```python
import torch

def _softmax(x, axis=-1):
    return torch.softmax(x, dim=axis)
def _gelu(x):
    return torch.nn.functional.gelu(x, approximate="tanh")
def _silu(x):
    return torch.nn.functional.silu(x)
def _sigmoid(x):
    return torch.sigmoid(x)
def _layernorm(x, axis=-1, eps=1e-5):
    m = x.mean(dim=axis, keepdim=True)
    v = x.var(dim=axis, keepdim=True, unbiased=False)
    return (x - m) / torch.sqrt(v + eps)
def _scatter_add(tgt, idx, src, axis=0):
    return tgt.clone().index_add_(axis, idx, src)
def _segment_sum(src, seg, n):
    out = torch.zeros((n,) + src.shape[1:], dtype=src.dtype)
    return out.index_add_(0, seg, src)
def _pad(x, pw):
    flat = tuple(v for pair in reversed(pw) for v in pair)
    return torch.nn.functional.pad(x, flat)

kernel_name = 'concat_heads__gqa_block_cached__gqa_block_cached__near_ridge'

def setup_inputs():

    _w = (lambda a: (lambda t: t.to(torch.bfloat16) if t.is_floating_point() else t)(torch.as_tensor(a)))
    def _A_setup():
        B, Sq, D = 8, 96, 448
        Hq, Hkv, Sk, Dh = 16, 8, 1024, 256
        assert Hq % Hkv == 0, (Hq, Hkv)
        return {
            "x": _w((lambda *s: torch.randn(*s, dtype=torch.bfloat16) * 0.8)(B, Sq, D)),
            "k_cache": _w((lambda *s: torch.randn(*s, dtype=torch.bfloat16) * 0.8)(B, Hkv, Sk, Dh)),
            "v_cache": _w((lambda *s: torch.randn(*s, dtype=torch.bfloat16) * 0.05)(B, Hkv, Sk, Dh)),
            "wq": _w((lambda *s: torch.randn(*s, dtype=torch.bfloat16) * 0.8)(D, Hq * Dh) * (D ** -0.5)),
            "wo": _w((lambda *s: torch.randn(*s, dtype=torch.bfloat16) * 0.05)(Hq * Dh, D) * ((Hq * Dh) ** -0.5)),
        }
    _A_in = _A_setup()

    def _B_setup():
        B, Sq, D = 8, 96, 448
        Hq, Hkv, Sk, Dh = 16, 8, 1024, 256
        assert Hq % Hkv == 0, (Hq, Hkv)
        return {
            "x": _w((lambda *s: torch.randn(*s, dtype=torch.bfloat16) * 0.8)(B, Sq, D)),
            "k_cache": _w((lambda *s: torch.randn(*s, dtype=torch.bfloat16) * 0.8)(B, Hkv, Sk, Dh)),
            "v_cache": _w((lambda *s: torch.randn(*s, dtype=torch.bfloat16) * 0.05)(B, Hkv, Sk, Dh)),
            "wq": _w((lambda *s: torch.randn(*s, dtype=torch.bfloat16) * 0.8)(D, Hq * Dh) * (D ** -0.5)),
            "wo": _w((lambda *s: torch.randn(*s, dtype=torch.bfloat16) * 0.05)(Hq * Dh, D) * ((Hq * Dh) ** -0.5)),
        }
    _B_in = _B_setup()

    return {
        "A_x": _A_in["x"],
        "A_k_cache": _A_in["k_cache"],
        "A_v_cache": _A_in["v_cache"],
        "A_wq": _A_in["wq"],
        "A_wo": _A_in["wo"],
        "B_x": _B_in["x"],
        "B_k_cache": _B_in["k_cache"],
        "B_v_cache": _B_in["v_cache"],
        "B_wq": _B_in["wq"],
        "B_wo": _B_in["wo"],
    }

def reference(A_x, A_k_cache, A_v_cache, A_wq, A_wo, B_x, B_k_cache, B_v_cache, B_wq, B_wo):
    def _A_ref(x, k_cache, v_cache, wq, wo):
        B, Sq, D = x.shape
        Hq, Dh = 16, 256
        Hkv = k_cache.shape[1]
        rep = Hq // Hkv
        q = (lambda x, *d: x.permute(*d))((x @ wq).reshape(B, Sq, Hq, Dh), 0, 2, 1, 3)
        k = (lambda x, n, axis: torch.repeat_interleave(x, n, dim=axis))(k_cache, rep, axis=1)
        v = (lambda x, n, axis: torch.repeat_interleave(x, n, dim=axis))(v_cache, rep, axis=1)
        scores = torch.einsum("bhqd,bhkd->bhqk", q, k) * (Dh ** -0.5)
        p = _softmax(scores, axis=-1)
        o = torch.einsum("bhqk,bhkd->bhqd", p, v)
        return (lambda x, *d: x.permute(*d))(o, 0, 2, 1, 3).reshape(B, Sq, Hq * Dh) @ wo

    def _B_ref(x, k_cache, v_cache, wq, wo):
        B, Sq, D = x.shape
        Hq, Dh = 16, 256
        Hkv = k_cache.shape[1]
        rep = Hq // Hkv
        q = (lambda x, *d: x.permute(*d))((x @ wq).reshape(B, Sq, Hq, Dh), 0, 2, 1, 3)
        k = (lambda x, n, axis: torch.repeat_interleave(x, n, dim=axis))(k_cache, rep, axis=1)
        v = (lambda x, n, axis: torch.repeat_interleave(x, n, dim=axis))(v_cache, rep, axis=1)
        scores = torch.einsum("bhqd,bhkd->bhqk", q, k) * (Dh ** -0.5)
        p = _softmax(scores, axis=-1)
        o = torch.einsum("bhqk,bhkd->bhqd", p, v)
        return (lambda x, *d: x.permute(*d))(o, 0, 2, 1, 3).reshape(B, Sq, Hq * Dh) @ wo

    a = _A_ref(A_x, A_k_cache, A_v_cache, A_wq, A_wo)
    b = _B_ref(B_x, B_k_cache, B_v_cache, B_wq, B_wo)
    return torch.concatenate([a, b], axis=-1)
```

```cpp
#include <cuda_runtime.h>
#include <cuda_bf16.h>
#include <cuda.h>
#include <stdint.h>

namespace {

constexpr int SQ = 96, DM = 448, SK = 1024;
constexpr int NSLOT = 8, SLOT = 16384;
constexpr int OFF_RING = 98304;
constexpr int OFF_BAR = OFF_RING + NSLOT * SLOT;
constexpr int SMEM_BYTES = OFF_BAR + 512;
constexpr int QCH = 24576;
constexpr int XCH = 12288;
constexpr int L_KV = 28, L_WO = 92, L_END = 120;
constexpr int NT = 32;
#define ON1 240
constexpr int N1 = ON1, N2 = 256 - N1;

struct Params {
  CUtensorMap m[10];
};

__device__ uint4 g_part[16 * 7 * 8 * 768];
__device__ uint32_t g_flag[16 * 7 * 4 * 8];
#define TRACE(i)

template<int TA, int TB> __device__ __forceinline__ void wgmma_ss_n32(float (&d)[16], uint64_t da, uint64_t db, int sd) {
  asm volatile("{\n.reg .pred p;\nsetp.ne.b32 p, %18, 0;\n"
   "wgmma.mma_async.sync.aligned.m64n32k16.f32.bf16.bf16 {"
   "%0, %1, %2, %3, %4, %5, %6, %7, %8, %9, %10, %11, %12, %13, %14, %15"
   "}, %16, %17, p, 1, 1, %19, %20;\n}\n"
   : "+f"(d[0]), "+f"(d[1]), "+f"(d[2]), "+f"(d[3]), "+f"(d[4]), "+f"(d[5]), "+f"(d[6]), "+f"(d[7]),
     "+f"(d[8]), "+f"(d[9]), "+f"(d[10]), "+f"(d[11]), "+f"(d[12]), "+f"(d[13]), "+f"(d[14]), "+f"(d[15])
   : "l"(da), "l"(db), "r"(sd), "n"(TA), "n"(TB));
}
template<int TA, int TB> __device__ __forceinline__ void wgmma_ss_n96(float (&d)[48], uint64_t da, uint64_t db, int sd) {
  asm volatile("{\n.reg .pred p;\nsetp.ne.b32 p, %50, 0;\n"
   "wgmma.mma_async.sync.aligned.m64n96k16.f32.bf16.bf16 {"
   "%0, %1, %2, %3, %4, %5, %6, %7, %8, %9, %10, %11, %12, %13, %14, %15, "
   "%16, %17, %18, %19, %20, %21, %22, %23, %24, %25, %26, %27, %28, %29, %30, %31, "
   "%32, %33, %34, %35, %36, %37, %38, %39, %40, %41, %42, %43, %44, %45, %46, %47"
   "}, %48, %49, p, 1, 1, %51, %52;\n}\n"
   : "+f"(d[0]), "+f"(d[1]), "+f"(d[2]), "+f"(d[3]), "+f"(d[4]), "+f"(d[5]), "+f"(d[6]), "+f"(d[7]),
     "+f"(d[8]), "+f"(d[9]), "+f"(d[10]), "+f"(d[11]), "+f"(d[12]), "+f"(d[13]), "+f"(d[14]), "+f"(d[15]),
     "+f"(d[16]), "+f"(d[17]), "+f"(d[18]), "+f"(d[19]), "+f"(d[20]), "+f"(d[21]), "+f"(d[22]), "+f"(d[23]),
     "+f"(d[24]), "+f"(d[25]), "+f"(d[26]), "+f"(d[27]), "+f"(d[28]), "+f"(d[29]), "+f"(d[30]), "+f"(d[31]),
     "+f"(d[32]), "+f"(d[33]), "+f"(d[34]), "+f"(d[35]), "+f"(d[36]), "+f"(d[37]), "+f"(d[38]), "+f"(d[39]),
     "+f"(d[40]), "+f"(d[41]), "+f"(d[42]), "+f"(d[43]), "+f"(d[44]), "+f"(d[45]), "+f"(d[46]), "+f"(d[47])
   : "l"(da), "l"(db), "r"(sd), "n"(TA), "n"(TB));
}
template<int TA, int TB> __device__ __forceinline__ void wgmma_ss_n256(float (&d)[128], uint64_t da, uint64_t db, int sd) {
  asm volatile("{\n.reg .pred p;\nsetp.ne.b32 p, %130, 0;\n"
   "wgmma.mma_async.sync.aligned.m64n256k16.f32.bf16.bf16 {"
   "%0, %1, %2, %3, %4, %5, %6, %7, %8, %9, %10, %11, %12, %13, %14, %15, "
   "%16, %17, %18, %19, %20, %21, %22, %23, %24, %25, %26, %27, %28, %29, %30, %31, "
   "%32, %33, %34, %35, %36, %37, %38, %39, %40, %41, %42, %43, %44, %45, %46, %47, "
   "%48, %49, %50, %51, %52, %53, %54, %55, %56, %57, %58, %59, %60, %61, %62, %63, "
   "%64, %65, %66, %67, %68, %69, %70, %71, %72, %73, %74, %75, %76, %77, %78, %79, "
   "%80, %81, %82, %83, %84, %85, %86, %87, %88, %89, %90, %91, %92, %93, %94, %95, "
   "%96, %97, %98, %99, %100, %101, %102, %103, %104, %105, %106, %107, %108, %109, %110, %111, "
   "%112, %113, %114, %115, %116, %117, %118, %119, %120, %121, %122, %123, %124, %125, %126, %127"
   "}, %128, %129, p, 1, 1, %131, %132;\n}\n"
   : "+f"(d[0]), "+f"(d[1]), "+f"(d[2]), "+f"(d[3]), "+f"(d[4]), "+f"(d[5]), "+f"(d[6]), "+f"(d[7]),
     "+f"(d[8]), "+f"(d[9]), "+f"(d[10]), "+f"(d[11]), "+f"(d[12]), "+f"(d[13]), "+f"(d[14]), "+f"(d[15]),
     "+f"(d[16]), "+f"(d[17]), "+f"(d[18]), "+f"(d[19]), "+f"(d[20]), "+f"(d[21]), "+f"(d[22]), "+f"(d[23]),
     "+f"(d[24]), "+f"(d[25]), "+f"(d[26]), "+f"(d[27]), "+f"(d[28]), "+f"(d[29]), "+f"(d[30]), "+f"(d[31]),
     "+f"(d[32]), "+f"(d[33]), "+f"(d[34]), "+f"(d[35]), "+f"(d[36]), "+f"(d[37]), "+f"(d[38]), "+f"(d[39]),
     "+f"(d[40]), "+f"(d[41]), "+f"(d[42]), "+f"(d[43]), "+f"(d[44]), "+f"(d[45]), "+f"(d[46]), "+f"(d[47]),
     "+f"(d[48]), "+f"(d[49]), "+f"(d[50]), "+f"(d[51]), "+f"(d[52]), "+f"(d[53]), "+f"(d[54]), "+f"(d[55]),
     "+f"(d[56]), "+f"(d[57]), "+f"(d[58]), "+f"(d[59]), "+f"(d[60]), "+f"(d[61]), "+f"(d[62]), "+f"(d[63]),
     "+f"(d[64]), "+f"(d[65]), "+f"(d[66]), "+f"(d[67]), "+f"(d[68]), "+f"(d[69]), "+f"(d[70]), "+f"(d[71]),
     "+f"(d[72]), "+f"(d[73]), "+f"(d[74]), "+f"(d[75]), "+f"(d[76]), "+f"(d[77]), "+f"(d[78]), "+f"(d[79]),
     "+f"(d[80]), "+f"(d[81]), "+f"(d[82]), "+f"(d[83]), "+f"(d[84]), "+f"(d[85]), "+f"(d[86]), "+f"(d[87]),
     "+f"(d[88]), "+f"(d[89]), "+f"(d[90]), "+f"(d[91]), "+f"(d[92]), "+f"(d[93]), "+f"(d[94]), "+f"(d[95]),
     "+f"(d[96]), "+f"(d[97]), "+f"(d[98]), "+f"(d[99]), "+f"(d[100]), "+f"(d[101]), "+f"(d[102]), "+f"(d[103]),
     "+f"(d[104]), "+f"(d[105]), "+f"(d[106]), "+f"(d[107]), "+f"(d[108]), "+f"(d[109]), "+f"(d[110]), "+f"(d[111]),
     "+f"(d[112]), "+f"(d[113]), "+f"(d[114]), "+f"(d[115]), "+f"(d[116]), "+f"(d[117]), "+f"(d[118]), "+f"(d[119]),
     "+f"(d[120]), "+f"(d[121]), "+f"(d[122]), "+f"(d[123]), "+f"(d[124]), "+f"(d[125]), "+f"(d[126]), "+f"(d[127])
   : "l"(da), "l"(db), "r"(sd), "n"(TA), "n"(TB));
}
template<int TB> __device__ __forceinline__ void wgmma_rs_n8(float (&d)[4], uint32_t a0, uint32_t a1, uint32_t a2, uint32_t a3, uint64_t db, int sd) {
  asm volatile("{\n.reg .pred p;\nsetp.ne.b32 p, %9, 0;\n"
   "wgmma.mma_async.sync.aligned.m64n8k16.f32.bf16.bf16 {"
   "%0, %1, %2, %3"
   "}, {%4, %5, %6, %7}, %8, p, 1, 1, %10;\n}\n"
   : "+f"(d[0]), "+f"(d[1]), "+f"(d[2]), "+f"(d[3])
   : "r"(a0), "r"(a1), "r"(a2), "r"(a3), "l"(db), "r"(sd), "n"(TB));
}
template<int TB> __device__ __forceinline__ void wgmma_rs_n16(float (&d)[8], uint32_t a0, uint32_t a1, uint32_t a2, uint32_t a3, uint64_t db, int sd) {
  asm volatile("{\n.reg .pred p;\nsetp.ne.b32 p, %13, 0;\n"
   "wgmma.mma_async.sync.aligned.m64n16k16.f32.bf16.bf16 {"
   "%0, %1, %2, %3, %4, %5, %6, %7"
   "}, {%8, %9, %10, %11}, %12, p, 1, 1, %14;\n}\n"
   : "+f"(d[0]), "+f"(d[1]), "+f"(d[2]), "+f"(d[3]), "+f"(d[4]), "+f"(d[5]), "+f"(d[6]), "+f"(d[7])
   : "r"(a0), "r"(a1), "r"(a2), "r"(a3), "l"(db), "r"(sd), "n"(TB));
}
template<int TB> __device__ __forceinline__ void wgmma_rs_n32(float (&d)[16], uint32_t a0, uint32_t a1, uint32_t a2, uint32_t a3, uint64_t db, int sd) {
  asm volatile("{\n.reg .pred p;\nsetp.ne.b32 p, %21, 0;\n"
   "wgmma.mma_async.sync.aligned.m64n32k16.f32.bf16.bf16 {"
   "%0, %1, %2, %3, %4, %5, %6, %7, %8, %9, %10, %11, %12, %13, %14, %15"
   "}, {%16, %17, %18, %19}, %20, p, 1, 1, %22;\n}\n"
   : "+f"(d[0]), "+f"(d[1]), "+f"(d[2]), "+f"(d[3]), "+f"(d[4]), "+f"(d[5]), "+f"(d[6]), "+f"(d[7]),
     "+f"(d[8]), "+f"(d[9]), "+f"(d[10]), "+f"(d[11]), "+f"(d[12]), "+f"(d[13]), "+f"(d[14]), "+f"(d[15])
   : "r"(a0), "r"(a1), "r"(a2), "r"(a3), "l"(db), "r"(sd), "n"(TB));
}
template<int TB> __device__ __forceinline__ void wgmma_rs_n224(float (&d)[112], uint32_t a0, uint32_t a1, uint32_t a2, uint32_t a3, uint64_t db, int sd) {
  asm volatile("{\n.reg .pred p;\nsetp.ne.b32 p, %117, 0;\n"
   "wgmma.mma_async.sync.aligned.m64n224k16.f32.bf16.bf16 {"
   "%0, %1, %2, %3, %4, %5, %6, %7, %8, %9, %10, %11, %12, %13, %14, %15, "
   "%16, %17, %18, %19, %20, %21, %22, %23, %24, %25, %26, %27, %28, %29, %30, %31, "
   "%32, %33, %34, %35, %36, %37, %38, %39, %40, %41, %42, %43, %44, %45, %46, %47, "
   "%48, %49, %50, %51, %52, %53, %54, %55, %56, %57, %58, %59, %60, %61, %62, %63, "
   "%64, %65, %66, %67, %68, %69, %70, %71, %72, %73, %74, %75, %76, %77, %78, %79, "
   "%80, %81, %82, %83, %84, %85, %86, %87, %88, %89, %90, %91, %92, %93, %94, %95, "
   "%96, %97, %98, %99, %100, %101, %102, %103, %104, %105, %106, %107, %108, %109, %110, %111"
   "}, {%112, %113, %114, %115}, %116, p, 1, 1, %118;\n}\n"
   : "+f"(d[0]), "+f"(d[1]), "+f"(d[2]), "+f"(d[3]), "+f"(d[4]), "+f"(d[5]), "+f"(d[6]), "+f"(d[7]),
     "+f"(d[8]), "+f"(d[9]), "+f"(d[10]), "+f"(d[11]), "+f"(d[12]), "+f"(d[13]), "+f"(d[14]), "+f"(d[15]),
     "+f"(d[16]), "+f"(d[17]), "+f"(d[18]), "+f"(d[19]), "+f"(d[20]), "+f"(d[21]), "+f"(d[22]), "+f"(d[23]),
     "+f"(d[24]), "+f"(d[25]), "+f"(d[26]), "+f"(d[27]), "+f"(d[28]), "+f"(d[29]), "+f"(d[30]), "+f"(d[31]),
     "+f"(d[32]), "+f"(d[33]), "+f"(d[34]), "+f"(d[35]), "+f"(d[36]), "+f"(d[37]), "+f"(d[38]), "+f"(d[39]),
     "+f"(d[40]), "+f"(d[41]), "+f"(d[42]), "+f"(d[43]), "+f"(d[44]), "+f"(d[45]), "+f"(d[46]), "+f"(d[47]),
     "+f"(d[48]), "+f"(d[49]), "+f"(d[50]), "+f"(d[51]), "+f"(d[52]), "+f"(d[53]), "+f"(d[54]), "+f"(d[55]),
     "+f"(d[56]), "+f"(d[57]), "+f"(d[58]), "+f"(d[59]), "+f"(d[60]), "+f"(d[61]), "+f"(d[62]), "+f"(d[63]),
     "+f"(d[64]), "+f"(d[65]), "+f"(d[66]), "+f"(d[67]), "+f"(d[68]), "+f"(d[69]), "+f"(d[70]), "+f"(d[71]),
     "+f"(d[72]), "+f"(d[73]), "+f"(d[74]), "+f"(d[75]), "+f"(d[76]), "+f"(d[77]), "+f"(d[78]), "+f"(d[79]),
     "+f"(d[80]), "+f"(d[81]), "+f"(d[82]), "+f"(d[83]), "+f"(d[84]), "+f"(d[85]), "+f"(d[86]), "+f"(d[87]),
     "+f"(d[88]), "+f"(d[89]), "+f"(d[90]), "+f"(d[91]), "+f"(d[92]), "+f"(d[93]), "+f"(d[94]), "+f"(d[95]),
     "+f"(d[96]), "+f"(d[97]), "+f"(d[98]), "+f"(d[99]), "+f"(d[100]), "+f"(d[101]), "+f"(d[102]), "+f"(d[103]),
     "+f"(d[104]), "+f"(d[105]), "+f"(d[106]), "+f"(d[107]), "+f"(d[108]), "+f"(d[109]), "+f"(d[110]), "+f"(d[111])
   : "r"(a0), "r"(a1), "r"(a2), "r"(a3), "l"(db), "r"(sd), "n"(TB));
}
template<int TB> __device__ __forceinline__ void wgmma_rs_n240(float (&d)[120], uint32_t a0, uint32_t a1, uint32_t a2, uint32_t a3, uint64_t db, int sd) {
  asm volatile("{\n.reg .pred p;\nsetp.ne.b32 p, %125, 0;\n"
   "wgmma.mma_async.sync.aligned.m64n240k16.f32.bf16.bf16 {"
   "%0, %1, %2, %3, %4, %5, %6, %7, %8, %9, %10, %11, %12, %13, %14, %15, "
   "%16, %17, %18, %19, %20, %21, %22, %23, %24, %25, %26, %27, %28, %29, %30, %31, "
   "%32, %33, %34, %35, %36, %37, %38, %39, %40, %41, %42, %43, %44, %45, %46, %47, "
   "%48, %49, %50, %51, %52, %53, %54, %55, %56, %57, %58, %59, %60, %61, %62, %63, "
   "%64, %65, %66, %67, %68, %69, %70, %71, %72, %73, %74, %75, %76, %77, %78, %79, "
   "%80, %81, %82, %83, %84, %85, %86, %87, %88, %89, %90, %91, %92, %93, %94, %95, "
   "%96, %97, %98, %99, %100, %101, %102, %103, %104, %105, %106, %107, %108, %109, %110, %111, "
   "%112, %113, %114, %115, %116, %117, %118, %119"
   "}, {%120, %121, %122, %123}, %124, p, 1, 1, %126;\n}\n"
   : "+f"(d[0]), "+f"(d[1]), "+f"(d[2]), "+f"(d[3]), "+f"(d[4]), "+f"(d[5]), "+f"(d[6]), "+f"(d[7]),
     "+f"(d[8]), "+f"(d[9]), "+f"(d[10]), "+f"(d[11]), "+f"(d[12]), "+f"(d[13]), "+f"(d[14]), "+f"(d[15]),
     "+f"(d[16]), "+f"(d[17]), "+f"(d[18]), "+f"(d[19]), "+f"(d[20]), "+f"(d[21]), "+f"(d[22]), "+f"(d[23]),
     "+f"(d[24]), "+f"(d[25]), "+f"(d[26]), "+f"(d[27]), "+f"(d[28]), "+f"(d[29]), "+f"(d[30]), "+f"(d[31]),
     "+f"(d[32]), "+f"(d[33]), "+f"(d[34]), "+f"(d[35]), "+f"(d[36]), "+f"(d[37]), "+f"(d[38]), "+f"(d[39]),
     "+f"(d[40]), "+f"(d[41]), "+f"(d[42]), "+f"(d[43]), "+f"(d[44]), "+f"(d[45]), "+f"(d[46]), "+f"(d[47]),
     "+f"(d[48]), "+f"(d[49]), "+f"(d[50]), "+f"(d[51]), "+f"(d[52]), "+f"(d[53]), "+f"(d[54]), "+f"(d[55]),
     "+f"(d[56]), "+f"(d[57]), "+f"(d[58]), "+f"(d[59]), "+f"(d[60]), "+f"(d[61]), "+f"(d[62]), "+f"(d[63]),
     "+f"(d[64]), "+f"(d[65]), "+f"(d[66]), "+f"(d[67]), "+f"(d[68]), "+f"(d[69]), "+f"(d[70]), "+f"(d[71]),
     "+f"(d[72]), "+f"(d[73]), "+f"(d[74]), "+f"(d[75]), "+f"(d[76]), "+f"(d[77]), "+f"(d[78]), "+f"(d[79]),
     "+f"(d[80]), "+f"(d[81]), "+f"(d[82]), "+f"(d[83]), "+f"(d[84]), "+f"(d[85]), "+f"(d[86]), "+f"(d[87]),
     "+f"(d[88]), "+f"(d[89]), "+f"(d[90]), "+f"(d[91]), "+f"(d[92]), "+f"(d[93]), "+f"(d[94]), "+f"(d[95]),
     "+f"(d[96]), "+f"(d[97]), "+f"(d[98]), "+f"(d[99]), "+f"(d[100]), "+f"(d[101]), "+f"(d[102]), "+f"(d[103]),
     "+f"(d[104]), "+f"(d[105]), "+f"(d[106]), "+f"(d[107]), "+f"(d[108]), "+f"(d[109]), "+f"(d[110]), "+f"(d[111]),
     "+f"(d[112]), "+f"(d[113]), "+f"(d[114]), "+f"(d[115]), "+f"(d[116]), "+f"(d[117]), "+f"(d[118]), "+f"(d[119])
   : "r"(a0), "r"(a1), "r"(a2), "r"(a3), "l"(db), "r"(sd), "n"(TB));
}
template<int TB> __device__ __forceinline__ void wgmma_rs_n248(float (&d)[124], uint32_t a0, uint32_t a1, uint32_t a2, uint32_t a3, uint64_t db, int sd) {
  asm volatile("{\n.reg .pred p;\nsetp.ne.b32 p, %129, 0;\n"
   "wgmma.mma_async.sync.aligned.m64n248k16.f32.bf16.bf16 {"
   "%0, %1, %2, %3, %4, %5, %6, %7, %8, %9, %10, %11, %12, %13, %14, %15, "
   "%16, %17, %18, %19, %20, %21, %22, %23, %24, %25, %26, %27, %28, %29, %30, %31, "
   "%32, %33, %34, %35, %36, %37, %38, %39, %40, %41, %42, %43, %44, %45, %46, %47, "
   "%48, %49, %50, %51, %52, %53, %54, %55, %56, %57, %58, %59, %60, %61, %62, %63, "
   "%64, %65, %66, %67, %68, %69, %70, %71, %72, %73, %74, %75, %76, %77, %78, %79, "
   "%80, %81, %82, %83, %84, %85, %86, %87, %88, %89, %90, %91, %92, %93, %94, %95, "
   "%96, %97, %98, %99, %100, %101, %102, %103, %104, %105, %106, %107, %108, %109, %110, %111, "
   "%112, %113, %114, %115, %116, %117, %118, %119, %120, %121, %122, %123"
   "}, {%124, %125, %126, %127}, %128, p, 1, 1, %130;\n}\n"
   : "+f"(d[0]), "+f"(d[1]), "+f"(d[2]), "+f"(d[3]), "+f"(d[4]), "+f"(d[5]), "+f"(d[6]), "+f"(d[7]),
     "+f"(d[8]), "+f"(d[9]), "+f"(d[10]), "+f"(d[11]), "+f"(d[12]), "+f"(d[13]), "+f"(d[14]), "+f"(d[15]),
     "+f"(d[16]), "+f"(d[17]), "+f"(d[18]), "+f"(d[19]), "+f"(d[20]), "+f"(d[21]), "+f"(d[22]), "+f"(d[23]),
     "+f"(d[24]), "+f"(d[25]), "+f"(d[26]), "+f"(d[27]), "+f"(d[28]), "+f"(d[29]), "+f"(d[30]), "+f"(d[31]),
     "+f"(d[32]), "+f"(d[33]), "+f"(d[34]), "+f"(d[35]), "+f"(d[36]), "+f"(d[37]), "+f"(d[38]), "+f"(d[39]),
     "+f"(d[40]), "+f"(d[41]), "+f"(d[42]), "+f"(d[43]), "+f"(d[44]), "+f"(d[45]), "+f"(d[46]), "+f"(d[47]),
     "+f"(d[48]), "+f"(d[49]), "+f"(d[50]), "+f"(d[51]), "+f"(d[52]), "+f"(d[53]), "+f"(d[54]), "+f"(d[55]),
     "+f"(d[56]), "+f"(d[57]), "+f"(d[58]), "+f"(d[59]), "+f"(d[60]), "+f"(d[61]), "+f"(d[62]), "+f"(d[63]),
     "+f"(d[64]), "+f"(d[65]), "+f"(d[66]), "+f"(d[67]), "+f"(d[68]), "+f"(d[69]), "+f"(d[70]), "+f"(d[71]),
     "+f"(d[72]), "+f"(d[73]), "+f"(d[74]), "+f"(d[75]), "+f"(d[76]), "+f"(d[77]), "+f"(d[78]), "+f"(d[79]),
     "+f"(d[80]), "+f"(d[81]), "+f"(d[82]), "+f"(d[83]), "+f"(d[84]), "+f"(d[85]), "+f"(d[86]), "+f"(d[87]),
     "+f"(d[88]), "+f"(d[89]), "+f"(d[90]), "+f"(d[91]), "+f"(d[92]), "+f"(d[93]), "+f"(d[94]), "+f"(d[95]),
     "+f"(d[96]), "+f"(d[97]), "+f"(d[98]), "+f"(d[99]), "+f"(d[100]), "+f"(d[101]), "+f"(d[102]), "+f"(d[103]),
     "+f"(d[104]), "+f"(d[105]), "+f"(d[106]), "+f"(d[107]), "+f"(d[108]), "+f"(d[109]), "+f"(d[110]), "+f"(d[111]),
     "+f"(d[112]), "+f"(d[113]), "+f"(d[114]), "+f"(d[115]), "+f"(d[116]), "+f"(d[117]), "+f"(d[118]), "+f"(d[119]),
     "+f"(d[120]), "+f"(d[121]), "+f"(d[122]), "+f"(d[123])
   : "r"(a0), "r"(a1), "r"(a2), "r"(a3), "l"(db), "r"(sd), "n"(TB));
}

__device__ __forceinline__ void mbar_init(uint32_t a, uint32_t c) { asm volatile("mbarrier.init.shared::cta.b64 [%0], %1;" ::"r"(a), "r"(c) : "memory"); }
__device__ __forceinline__ void mbar_expect_tx(uint32_t a, uint32_t b) { asm volatile("mbarrier.arrive.expect_tx.shared::cta.b64 _, [%0], %1;" ::"r"(a), "r"(b) : "memory"); }
__device__ __forceinline__ void mbar_arrive(uint32_t a) { asm volatile("mbarrier.arrive.shared::cta.b64 _, [%0];" ::"r"(a) : "memory"); }
__device__ __forceinline__ void mbar_wait(uint32_t a, uint32_t p) {
  asm volatile("{\n.reg .pred P1;\n.reg .u32 c;\nmov.u32 c, 0;\nWAIT_LOOP:\n"
               "mbarrier.try_wait.parity.shared::cta.b64 P1, [%0], %1;\n@P1 bra DONE;\n"
               "add.u32 c, c, 1;\nsetp.lt.u32 P1, c, 4000000;\n@P1 bra WAIT_LOOP;\ntrap;\nDONE:\n}" ::"r"(a), "r"(p) : "memory");
}
__device__ __forceinline__ void tma3d(uint32_t dst, const CUtensorMap* map, int c1, int c2, uint32_t bar) {
  asm volatile("cp.async.bulk.tensor.3d.shared::cluster.global.mbarrier::complete_tx::bytes [%0], [%1, {%2, %3, %4}], [%5];"
               ::"r"(dst), "l"(map), "r"(0), "r"(c1), "r"(c2), "r"(bar) : "memory");
}
__device__ __forceinline__ uint32_t desc_lo(uint32_t addr, uint32_t lbo) { return ((addr & 0x3FFFF) >> 4) | ((lbo >> 4) << 16); }
__device__ __forceinline__ uint64_t desc_mk(uint32_t lo) { uint64_t d; asm("mov.b64 %0, {%1, %2};" : "=l"(d) : "r"(lo), "r"(0x40000040)); return d; }
#define WG_FENCE() asm volatile("wgmma.fence.sync.aligned;" ::: "memory")
#define WG_COMMIT() asm volatile("wgmma.commit_group.sync.aligned;" ::: "memory")
#define WG_WAIT(n) asm volatile("wgmma.wait_group.sync.aligned %0;" ::"n"(n) : "memory")
template <int N> __device__ __forceinline__ void fop(float (&d)[N]) {
#pragma unroll
  for (int i = 0; i < N; i++) asm volatile("" : "+f"(d[i])::"memory");
}
__device__ __forceinline__ uint32_t pack(float a, float b) { uint32_t r; asm("cvt.rn.bf16x2.f32 %0, %1, %2;" : "=r"(r) : "f"(b), "f"(a)); return r; }
__device__ __forceinline__ float ex2(float x) { float y; asm("ex2.approx.ftz.f32 %0, %1;" : "=f"(y) : "f"(x)); return y; }
__device__ __forceinline__ void nb_sync(int id, int n) { asm volatile("bar.sync %0, %1;" ::"r"(id), "r"(n) : "memory"); }
__device__ __forceinline__ void nb_arrive(int id, int n) { asm volatile("bar.arrive %0, %1;" ::"r"(id), "r"(n) : "memory"); }
__device__ __forceinline__ bool elect() { uint32_t p; asm volatile("{\n.reg .pred P;\nelect.sync _|P, 0xffffffff;\nselp.u32 %0,1,0,P;\n}" : "=r"(p)); return p; }
__device__ __forceinline__ void stsm4(uint32_t a, uint32_t r0, uint32_t r1, uint32_t r2, uint32_t r3) {
  asm volatile("stmatrix.sync.aligned.m8n8.x4.shared.b16 [%0], {%1,%2,%3,%4};" ::"r"(a), "r"(r0), "r"(r1), "r"(r2), "r"(r3) : "memory");
}
__device__ __forceinline__ void stsm4t(uint32_t a, uint32_t r0, uint32_t r1, uint32_t r2, uint32_t r3) {
  asm volatile("stmatrix.sync.aligned.m8n8.x4.trans.shared.b16 [%0], {%1,%2,%3,%4};" ::"r"(a), "r"(r0), "r"(r1), "r"(r2), "r"(r3) : "memory");
}
__device__ __forceinline__ void proxy_fence() { asm volatile("fence.proxy.async.shared::cta;" ::: "memory"); }
__device__ __forceinline__ float bf_lo(uint32_t v) { return __uint_as_float(v << 16); }
__device__ __forceinline__ float bf_hi(uint32_t v) { return __uint_as_float(v & 0xffff0000u); }

__global__ void __launch_bounds__(384, 1)
gqa_fused_kernel(const __grid_constant__ Params prm, __nv_bfloat16* __restrict__ out, uint32_t zero) {
  extern __shared__ __align__(1024) char smem[];
  const uint32_t sb = (uint32_t)__cvta_generic_to_shared(smem);
  const uint32_t full = sb + OFF_BAR, emptyQ = full + 64, emptyO = full + 128, xfull = full + 192, wofull = full + 256;
  const int warp = __shfl_sync(0xffffffff, threadIdx.x >> 5, 0);
  const int wg = warp >> 2, wiw = warp & 3, lane = threadIdx.x & 31;
  const int kvh = blockIdx.x & 7, bb = (blockIdx.x >> 3) & 7, blk = blockIdx.x >> 6;
  const CUtensorMap* maps = prm.m + blk * 5;
  const int kvrow0 = (bb * 8 + kvh) * SK;
  TRACE(0);

  auto issue_load = [&](int L) {
    uint32_t bar = full + 8 * (L & 7); const uint32_t dst = sb + OFF_RING + (L & 7) * SLOT;
    const CUtensorMap* mp; int c1, c2;
    if (L < L_KV) { mp = maps + 3; c1 = L * 16; c2 = kvh * 8; }
    else if (L < L_WO) { mp = maps + 1 + (L & 1); c1 = kvrow0 + ((L - L_KV) >> 1) * 32; c2 = 0; }
    else { int p = (L - L_WO) >> 2; int t = p + kvh + 1; if (kvh == 7) t = p; else if (t >= 7) t -= 7;
           mp = maps + 4; c1 = kvh * 512 + (L & 3) * 128; c2 = t; bar = wofull + 8 * (L - L_WO); }
    mbar_expect_tx(bar, SLOT);
    tma3d(dst, mp, c1, c2, bar);
  };

  if (threadIdx.x == 0) {
    if (sb & 1023) __trap();
    for (int i = 0; i < 8; i++) { mbar_init(full + 8 * i, 1); mbar_init(emptyQ + 8 * i, 12); mbar_init(emptyO + 8 * i, 4); }
    for (int i = 0; i < 7; i++) mbar_init(xfull + 8 * i, 1);
    for (int i = 0; i < 28; i++) mbar_init(wofull + 8 * i, 1);
    asm volatile("fence.mbarrier_init.release.cluster;" ::: "memory");
    mbar_expect_tx(xfull, XCH); tma3d(sb, maps, bb * SQ, 0, xfull);
    for (int i = 0; i < 4; i++) issue_load(i);
    mbar_expect_tx(xfull + 8, XCH); tma3d(sb + XCH, maps, bb * SQ, 1, xfull + 8);
    for (int i = 4; i < 8; i++) issue_load(i);
    for (int c = 2; c < 7; c++) { mbar_expect_tx(xfull + 8 * c, XCH); tma3d(sb + c * XCH, maps, bb * SQ, c, xfull + 8 * c); }
  }
  __syncthreads();
  TRACE(1);

  {
    const uint32_t ringlo = desc_lo(sb + OFF_RING, 2048);
    const uint32_t qrow = wg * 64 + wiw * 16 + (lane & 7) + ((lane >> 3) & 1) * 8;
    if (wg != 1) {
      float acc[128];
      const uint32_t xlo = desc_lo(sb + (wg ? 32 * 128 : 0), 16);
      const uint32_t blo = ringlo + (wg ? (8192 >> 4) : 0);
      for (int s = 0; s < L_KV; s++) {
        if ((s & 3) == 0) mbar_wait(xfull + 8 * (s >> 2), 0);
        mbar_wait(full + 8 * (s & 7), (s >> 3) & 1);
        WG_FENCE();
        wgmma_ss_n256<0, 1>(acc, desc_mk(xlo + (((s >> 2) * XCH + (s & 3) * 32) >> 4)), desc_mk(blo + (s & 7) * (SLOT >> 4)), s > 0);
        WG_COMMIT();
        if (warp == 0 && s >= 2) {
          if (elect()) { mbar_wait(emptyQ + 8 * ((s - 2) & 7), ((s - 2) >> 3) & 1); issue_load(s + 6); }
          __syncwarp();
        }
        WG_WAIT(1);
        if (s >= 1 && elect()) mbar_arrive(emptyQ + 8 * ((s - 1) & 7));
      }
      WG_WAIT(0); fop(acc);
      __syncthreads();
      if (threadIdx.x == 0) { issue_load(34); issue_load(35); }
      const uint32_t base = sb + qrow * 128;
#pragma unroll
      for (int j = 0; j < 32; j += 2) {
        const int g = j + (lane >> 4);
        stsm4(base + (j >> 3) * QCH + (((g & 7) ^ (lane & 7)) << 4), pack(acc[4 * j], acc[4 * j + 1]), pack(acc[4 * j + 2], acc[4 * j + 3]),
              pack(acc[4 * j + 4], acc[4 * j + 5]), pack(acc[4 * j + 6], acc[4 * j + 7]));
      }
    } else {
      float acc[8][16];
      const uint32_t xlo = desc_lo(sb, 16);
      for (int s = 0; s < L_KV; s++) {
        if ((s & 3) == 0) mbar_wait(xfull + 8 * (s >> 2), 0);
        mbar_wait(full + 8 * (s & 7), (s >> 3) & 1);
        WG_FENCE();
        const uint32_t alo = ringlo + (s & 7) * (SLOT >> 4), xs = xlo + (((s >> 2) * XCH + (s & 3) * 32) >> 4);
#pragma unroll
        for (int t = 0; t < 8; t++)
          wgmma_ss_n32<1, 0>(acc[t], desc_mk(alo + t * (2048 >> 4)), desc_mk(xs + (t < 4 ? (64 * 128 >> 4) : 0)), s > 0);
        WG_COMMIT();
        WG_WAIT(1);
        if (s >= 1 && elect()) mbar_arrive(emptyQ + 8 * ((s - 1) & 7));
      }
      WG_WAIT(0);
#pragma unroll
      for (int t = 0; t < 8; t++) fop(acc[t]);
      __syncthreads();
      const int g = 2 * wiw + ((lane >> 3) & 1);
      const uint32_t base = sb + (64 + (lane >> 4) * 8 + (lane & 7)) * 128 + ((g ^ (lane & 7)) << 4);
#pragma unroll
      for (int t = 0; t < 8; t++)
#pragma unroll
        for (int j = 0; j < 4; j += 2)
          stsm4t(base + (t & 3) * QCH + ((t >> 2) * 32 + j * 8) * 128, pack(acc[t][4 * j], acc[t][4 * j + 1]), pack(acc[t][4 * j + 2], acc[t][4 * j + 3]),
                 pack(acc[t][4 * j + 4], acc[t][4 * j + 5]), pack(acc[t][4 * j + 6], acc[t][4 * j + 7]));
    }
    proxy_fence();
    if (warp == 1) mbar_wait(full + 8 * (L_KV & 7), (L_KV >> 3) & 1);
    nb_sync(7 + wg, 128);
  }
  TRACE(2);

  {
    const uint32_t qlo = desc_lo(sb + wg * 8192, 16);
    float o[N1 / 2], park[N2 / 2];
#pragma unroll
    for (int i = 0; i < N1 / 2; i++) o[i] = 0.f;
#pragma unroll
    for (int i = 0; i < N2 / 2; i++) park[i] = 0.f;
    float m0 = -INFINITY, m1 = -INFINITY, l0 = 0.f, l1 = 0.f;
    const float c = 0.0625f * 1.4426950408889634f;
    for (int it = 0; it < NT; it++) {
      const int L = L_KV + 2 * it;
      float s[16];
      const uint32_t klo = desc_lo(sb + OFF_RING, 16) + (L & 7) * (SLOT >> 4);
      if (!(it == 0 && wg == 0)) nb_sync(1 + wg, 256);
      WG_FENCE();
#pragma unroll
      for (int kk = 0; kk < 16; kk++)
        wgmma_ss_n32<0, 0>(s, desc_mk(qlo + (((kk >> 2) * QCH + (kk & 3) * 32) >> 4)), desc_mk(klo + (((kk >> 2) * 4096 + (kk & 3) * 32) >> 4)), kk > 0);
      WG_COMMIT();
      if (it == 0 && wg == 0) nb_arrive(2, 256); else nb_arrive(4 + (wg == 0 ? 2 : wg - 1), 256);
      if (warp == 9 && it > 0) { if (elect()) issue_load(L + 7); __syncwarp(); }
      if (warp == 1) mbar_wait(full + 8 * ((L + 1) & 7), ((L + 1) >> 3) & 1);
      WG_WAIT(0); fop(s);
      float n0 = fmaxf(s[0], s[1]), n1 = fmaxf(s[2], s[3]);
#pragma unroll
      for (int i = 4; i < 16; i += 4) { n0 = fmaxf(n0, fmaxf(s[i], s[i + 1])); n1 = fmaxf(n1, fmaxf(s[i + 2], s[i + 3])); }
      if (__any_sync(0xffffffffu, (n0 > m0 + 8.f / c) || (n1 > m1 + 8.f / c))) {
        n0 = fmaxf(n0, m0); n1 = fmaxf(n1, m1);
        n0 = fmaxf(n0, __shfl_xor_sync(0xffffffffu, n0, 1)); n1 = fmaxf(n1, __shfl_xor_sync(0xffffffffu, n1, 1));
        n0 = fmaxf(n0, __shfl_xor_sync(0xffffffffu, n0, 2)); n1 = fmaxf(n1, __shfl_xor_sync(0xffffffffu, n1, 2));
        const float a0 = ex2((m0 - n0) * c), a1 = ex2((m1 - n1) * c);
        m0 = n0; m1 = n1; l0 *= a0; l1 *= a1;
#pragma unroll
        for (int i = 0; i < N1 / 2; i += 4) { o[i] *= a0; o[i + 1] *= a0; o[i + 2] *= a1; o[i + 3] *= a1; }
#pragma unroll
        for (int i = 0; i < N2 / 2; i += 4) { park[i] *= a0; park[i + 1] *= a0; park[i + 2] *= a1; park[i + 3] *= a1; }
      }
      uint32_t p[8];
      const float b0 = -m0 * c, b1 = -m1 * c;
#pragma unroll
      for (int i = 0; i < 16; i += 4) {
        const float e0 = ex2(fmaf(s[i], c, b0)), e1 = ex2(fmaf(s[i + 1], c, b0)), e2 = ex2(fmaf(s[i + 2], c, b1)), e3 = ex2(fmaf(s[i + 3], c, b1));
        l0 += e0 + e1; l1 += e2 + e3;
        p[i / 2] = pack(e0, e1); p[i / 2 + 1] = pack(e2, e3);
      }
      fop(o);
      const uint32_t vlo = desc_lo(sb + OFF_RING, 4096) + ((L + 1) & 7) * (SLOT >> 4);
      {
        uint32_t t = 0;
#pragma unroll
        for (int i = 0; i < 8; i++) t |= p[i];
        nb_sync(4 + wg + (t & zero), 256);
      }
      float o2[N2 / 2];
      WG_FENCE();
#pragma unroll
      for (int kk = 0; kk < 2; kk++) {
        const uint64_t db = desc_mk(vlo + ((kk * 2048) >> 4)), db2 = desc_mk(vlo + ((kk * 2048 + 3 * 4096 + (N1 - 192) * 2) >> 4));
        wgmma_rs_n240<1>(o, p[kk * 4], p[kk * 4 + 1], p[kk * 4 + 2], p[kk * 4 + 3], db, 1);
        wgmma_rs_n16<1>(o2, p[kk * 4], p[kk * 4 + 1], p[kk * 4 + 2], p[kk * 4 + 3], db2, kk);
      }
      WG_COMMIT();
      if (wg == 0 || it < NT - 1) nb_arrive(1 + (wg == 0 ? 2 : wg - 1), 256);
      else if (wg == 1) nb_arrive(6, 256);
      if (warp == 9) { if (elect()) issue_load(L + 8); __syncwarp(); }
      if (warp == 1 && it + 1 < NT) mbar_wait(full + 8 * ((L + 2) & 7), ((L + 2) >> 3) & 1);
      WG_WAIT(0); fop(o); fop(o2);
#pragma unroll
      for (int i = 0; i < N2 / 2; i++) park[i] += o2[i];
    }
    TRACE(3);
    l0 += __shfl_xor_sync(0xffffffffu, l0, 1); l1 += __shfl_xor_sync(0xffffffffu, l1, 1);
    l0 += __shfl_xor_sync(0xffffffffu, l0, 2); l1 += __shfl_xor_sync(0xffffffffu, l1, 2);
    const float r0 = 1.f / l0, r1 = 1.f / l1;
    const uint32_t base = sb + (wg * 64 + wiw * 16 + (lane & 7) + ((lane >> 3) & 1) * 8) * 128;
#pragma unroll
    for (int j = 0; j < 32; j += 2) {
      float v[8];
#pragma unroll
      for (int i = 0; i < 8; i++) { const int q = 4 * j + i; v[i] = (q < N1 / 2 ? o[q < N1 / 2 ? q : 0] : park[q >= N1 / 2 ? q - N1 / 2 : 0]) * ((i & 2) ? r1 : r0); }
      const int g = j + (lane >> 4);
      stsm4(base + (j >> 3) * QCH + (((g & 7) ^ (lane & 7)) << 4), pack(v[0], v[1]), pack(v[2], v[3]), pack(v[4], v[5]), pack(v[6], v[7]));
    }
    proxy_fence();
    __syncthreads();
    if (threadIdx.x == 0) issue_load(L_WO + 7);
  }
  TRACE(4);

  {
    const int grp = blockIdx.x >> 3;
    const uint32_t alo = desc_lo(sb + OFF_RING, 2048), olo = desc_lo(sb, 16);
    const int tw = threadIdx.x & 127;
    float sum[48];
    uint32_t done = 1u << kvh;
    auto gather = [&](bool block) {
      volatile uint32_t* fl = g_flag + ((grp * 7 + kvh) * 4 + wiw) * 8;
      int spins = 0;
      while (done != 0xffu) {
        uint32_t f = 0;
        if (lane < 8) asm volatile("ld.acquire.gpu.global.u32 %0, [%1];" : "=r"(f) : "l"(fl + lane) : "memory");
        uint32_t rdy = __ballot_sync(0xffffffffu, f != 0) & ~done;
        __syncwarp();
        if (rdy == 0) { if (!block) break; if (++spins > 20000000) __trap(); continue; }
        if (lane < 8 && ((rdy >> lane) & 1)) fl[lane] = 0;
        done |= rdy;
        while (rdy) {
          const int src = __ffs(rdy) - 1; rdy &= rdy - 1;
          const uint4* pp = g_part + ((grp * 7 + kvh) * 8 + src) * 768 + tw;
          uint4 v[6];
#pragma unroll
          for (int i = 0; i < 6; i++) v[i] = __ldcg(pp + i * 128);
#pragma unroll
          for (int i = 0; i < 6; i++) {
            sum[8 * i] += bf_lo(v[i].x); sum[8 * i + 1] += bf_hi(v[i].x); sum[8 * i + 2] += bf_lo(v[i].y); sum[8 * i + 3] += bf_hi(v[i].y);
            sum[8 * i + 4] += bf_lo(v[i].z); sum[8 * i + 5] += bf_hi(v[i].z); sum[8 * i + 6] += bf_lo(v[i].w); sum[8 * i + 7] += bf_hi(v[i].w);
          }
        }
        if (!block) break;
      }
    };
    for (int p = wg; p < 7; p += 3) {
      const bool own = (p == 6) && (kvh != 7);
      if (own) {
#pragma unroll
        for (int i = 0; i < 48; i++) sum[i] = 0.f;
        gather(false);
      }
      float acc[48];
#pragma unroll
      for (int q = 0; q < 4; q++) {
        const int L = L_WO + 4 * p + q;
        mbar_wait(wofull + 8 * (L - L_WO), 0);
        WG_FENCE();
#pragma unroll
        for (int ks = 0; ks < 8; ks++)
          wgmma_ss_n96<1, 0>(acc, desc_mk(alo + (L & 7) * (SLOT >> 4) + ks * (2048 >> 4)),
                             desc_mk(olo + (((2 * (q & 1) + (ks >> 2)) * QCH + (q >> 1) * XCH + (ks & 3) * 32) >> 4)), (q | ks) != 0);
        WG_COMMIT();
        if (q > 0) {
          WG_WAIT(1);
          if (L + 7 < L_END) {
            if (elect()) { mbar_arrive(emptyO + 8 * ((L - 1) & 7));
              if (wiw == 0) { mbar_wait(emptyO + 8 * ((L - 1) & 7), ((L - 1 - L_WO) >> 3) & 1); issue_load(L + 7); } }
            __syncwarp();
          }
        }
      }
      WG_WAIT(0); fop(acc);
      if (own) gather(true);
      { const int L = L_WO + 4 * p + 3;
        if (L + 8 < L_END) {
          if (elect()) { mbar_arrive(emptyO + 8 * (L & 7));
            if (wiw == 0) { mbar_wait(emptyO + 8 * (L & 7), ((L - L_WO) >> 3) & 1); issue_load(L + 8); } }
          __syncwarp();
        } }
      if (!own) {
        int t = p + kvh + 1; if (kvh == 7) t = p; else if (t >= 7) t -= 7;
        uint4* pp = g_part + ((grp * 7 + t) * 8 + kvh) * 768 + tw;
#pragma unroll
        for (int i = 0; i < 6; i++)
          __stcg(pp + i * 128, make_uint4(pack(acc[8 * i], acc[8 * i + 1]), pack(acc[8 * i + 2], acc[8 * i + 3]), pack(acc[8 * i + 4], acc[8 * i + 5]), pack(acc[8 * i + 6], acc[8 * i + 7])));
        __syncwarp();
        if (lane == 0) { __threadfence(); asm volatile("st.relaxed.gpu.global.u32 [%0], %1;" ::"l"(g_flag + ((grp * 7 + t) * 4 + wiw) * 8 + kvh), "r"(1u) : "memory"); }
      } else {
        nb_sync(7, 128);
        const uint32_t stg = sb + OFF_RING + 4 * SLOT + wiw * 4096;
        const int r = (lane >> 4) * 8 + (lane & 7), h = (lane >> 3) & 1;
#pragma unroll
        for (int j = 0; j < 12; j += 2)
          stsm4t(stg + (j * 8 + r) * 32 + ((h ^ ((r >> 2) & 1)) << 4),
                 pack(acc[4 * j] + sum[4 * j], acc[4 * j + 1] + sum[4 * j + 1]), pack(acc[4 * j + 2] + sum[4 * j + 2], acc[4 * j + 3] + sum[4 * j + 3]),
                 pack(acc[4 * j + 4] + sum[4 * j + 4], acc[4 * j + 5] + sum[4 * j + 5]), pack(acc[4 * j + 6] + sum[4 * j + 6], acc[4 * j + 7] + sum[4 * j + 7]));
        __syncwarp();
        __nv_bfloat16* ob = out + (size_t)(bb * SQ) * (2 * DM) + blk * DM + kvh * 64 + wiw * 16;
#pragma unroll
        for (int i = 0; i < 6; i++) {
          const int row = i * 16 + (lane >> 1), hh = lane & 1;
          uint4 v;
          asm volatile("ld.shared.v4.u32 {%0,%1,%2,%3}, [%4];" : "=r"(v.x), "=r"(v.y), "=r"(v.z), "=r"(v.w) : "r"(stg + row * 32 + ((hh ^ ((row >> 2) & 1)) << 4)));
          *reinterpret_cast<uint4*>(ob + (size_t)row * (2 * DM) + hh * 8) = v;
        }
      }
    }
  }
  TRACE(5);
}

typedef CUresult (*EncodeFn)(CUtensorMap*, CUtensorMapDataType, cuuint32_t, void*, const cuuint64_t*, const cuuint64_t*, const cuuint32_t*,
                             const cuuint32_t*, CUtensorMapInterleave, CUtensorMapSwizzle, CUtensorMapL2promotion, CUtensorMapFloatOOBfill);

void make_map(EncodeFn fn, CUtensorMap* m, void* ptr, uint64_t rows, uint64_t cols, uint32_t brows, uint32_t bchunks) {
  cuuint64_t dims[3] = {64, rows, cols / 64};
  cuuint64_t strides[2] = {cols * 2, 128};
  cuuint32_t box[3] = {64, brows, bchunks};
  cuuint32_t es[3] = {1, 1, 1};
  fn(m, CU_TENSOR_MAP_DATA_TYPE_BFLOAT16, 3, ptr, dims, strides, box, es, CU_TENSOR_MAP_INTERLEAVE_NONE, CU_TENSOR_MAP_SWIZZLE_128B,
     CU_TENSOR_MAP_L2_PROMOTION_L2_256B, CU_TENSOR_MAP_FLOAT_OOB_FILL_NONE);
}

}

extern "C" void kernel_launch(void* const* d_in, const int* in_sizes, int n_in, void* d_out, int out_size) {
  static EncodeFn fn = nullptr;
  if (!fn) {
    void* p = nullptr; cudaDriverEntryPointQueryResult qr;
    cudaGetDriverEntryPoint("cuTensorMapEncodeTiled", &p, cudaEnableDefault, &qr);
    fn = (EncodeFn)p;
    cudaFuncSetAttribute(gqa_fused_kernel, cudaFuncAttributeMaxDynamicSharedMemorySize, SMEM_BYTES);
  }
  Params prm;
  for (int b = 0; b < 2; b++) {
    make_map(fn, &prm.m[b * 5 + 0], d_in[b * 5 + 0], 768, 448, 96, 1);
    make_map(fn, &prm.m[b * 5 + 1], d_in[b * 5 + 1], 65536, 256, 32, 4);
    make_map(fn, &prm.m[b * 5 + 2], d_in[b * 5 + 2], 65536, 256, 32, 4);
    make_map(fn, &prm.m[b * 5 + 3], d_in[b * 5 + 3], 448, 4096, 16, 8);
    make_map(fn, &prm.m[b * 5 + 4], d_in[b * 5 + 4], 4096, 448, 128, 1);
  }
  gqa_fused_kernel<<<128, 384, SMEM_BYTES, cudaStreamPerThread>>>(prm, (__nv_bfloat16*)d_out, 0u);
}
```

```cpp
#define 8.in.cu
#define PF_C 0
#define PF_DEN 2
#define PF_N 8
#define PF_NUM 1
#define PF_OFF 2
#define PF_S0 9
#define PF_STR 6
#define PAIRMAP
#include <cuda_runtime.h>
#include <cuda_bf16.h>
#include <cuda.h>
#include <stdint.h>

namespace {

constexpr int SQ = 96, DM = 448, SK = 1024;
constexpr int SLOT = 16384;
constexpr int KVS = 24576;
constexpr int OFF_RING = 98304;
constexpr int OFF_BAR = OFF_RING + 8 * SLOT;
constexpr int SMEM_BYTES = OFF_BAR + 1792;
constexpr int QCH = 24576;
constexpr int XCH = 12288;
constexpr int NT = 22;
constexpr int NWO = 28;
#define WARM0 0
#define POLLMAX 0
#define ON1 224
constexpr int N1 = ON1, N2 = 256 - N1;

struct Params {
  CUtensorMap m[14];
  CUtensorMap mo;
  const char* kv[6];
};

__device__ uint4 g_part[16 * 7 * 8 * 768];
__device__ uint32_t g_epoch[16 * 32];
#define TRACE(i)
#define TRACEW(i, cond)

template<int TA, int TB> __device__ __forceinline__ void wgmma_ss_n16(float (&d)[8], uint64_t da, uint64_t db, int sd) {
  asm volatile("{\n.reg .pred p;\nsetp.ne.b32 p, %10, 0;\n"
   "wgmma.mma_async.sync.aligned.m64n16k16.f32.bf16.bf16 {"
   "%0, %1, %2, %3, %4, %5, %6, %7"
   "}, %8, %9, p, 1, 1, %11, %12;\n}\n"
   : "+f"(d[0]), "+f"(d[1]), "+f"(d[2]), "+f"(d[3]), "+f"(d[4]), "+f"(d[5]), "+f"(d[6]), "+f"(d[7])
   : "l"(da), "l"(db), "r"(sd), "n"(TA), "n"(TB));
}
template<int TA, int TB> __device__ __forceinline__ void wgmma_ss_n32(float (&d)[16], uint64_t da, uint64_t db, int sd) {
  asm volatile("{\n.reg .pred p;\nsetp.ne.b32 p, %18, 0;\n"
   "wgmma.mma_async.sync.aligned.m64n32k16.f32.bf16.bf16 {"
   "%0, %1, %2, %3, %4, %5, %6, %7, %8, %9, %10, %11, %12, %13, %14, %15"
   "}, %16, %17, p, 1, 1, %19, %20;\n}\n"
   : "+f"(d[0]), "+f"(d[1]), "+f"(d[2]), "+f"(d[3]), "+f"(d[4]), "+f"(d[5]), "+f"(d[6]), "+f"(d[7]),
     "+f"(d[8]), "+f"(d[9]), "+f"(d[10]), "+f"(d[11]), "+f"(d[12]), "+f"(d[13]), "+f"(d[14]), "+f"(d[15])
   : "l"(da), "l"(db), "r"(sd), "n"(TA), "n"(TB));
}
template<int TA, int TB> __device__ __forceinline__ void wgmma_ss_n48(float (&d)[24], uint64_t da, uint64_t db, int sd) {
  asm volatile("{\n.reg .pred p;\nsetp.ne.b32 p, %26, 0;\n"
   "wgmma.mma_async.sync.aligned.m64n48k16.f32.bf16.bf16 {"
   "%0, %1, %2, %3, %4, %5, %6, %7, %8, %9, %10, %11, %12, %13, %14, %15, "
   "%16, %17, %18, %19, %20, %21, %22, %23"
   "}, %24, %25, p, 1, 1, %27, %28;\n}\n"
   : "+f"(d[0]), "+f"(d[1]), "+f"(d[2]), "+f"(d[3]), "+f"(d[4]), "+f"(d[5]), "+f"(d[6]), "+f"(d[7]),
     "+f"(d[8]), "+f"(d[9]), "+f"(d[10]), "+f"(d[11]), "+f"(d[12]), "+f"(d[13]), "+f"(d[14]), "+f"(d[15]),
     "+f"(d[16]), "+f"(d[17]), "+f"(d[18]), "+f"(d[19]), "+f"(d[20]), "+f"(d[21]), "+f"(d[22]), "+f"(d[23])
   : "l"(da), "l"(db), "r"(sd), "n"(TA), "n"(TB));
}
template<int TA, int TB> __device__ __forceinline__ void wgmma_ss_n64(float (&d)[32], uint64_t da, uint64_t db, int sd) {
  asm volatile("{\n.reg .pred p;\nsetp.ne.b32 p, %34, 0;\n"
   "wgmma.mma_async.sync.aligned.m64n64k16.f32.bf16.bf16 {"
   "%0, %1, %2, %3, %4, %5, %6, %7, %8, %9, %10, %11, %12, %13, %14, %15, "
   "%16, %17, %18, %19, %20, %21, %22, %23, %24, %25, %26, %27, %28, %29, %30, %31"
   "}, %32, %33, p, 1, 1, %35, %36;\n}\n"
   : "+f"(d[0]), "+f"(d[1]), "+f"(d[2]), "+f"(d[3]), "+f"(d[4]), "+f"(d[5]), "+f"(d[6]), "+f"(d[7]),
     "+f"(d[8]), "+f"(d[9]), "+f"(d[10]), "+f"(d[11]), "+f"(d[12]), "+f"(d[13]), "+f"(d[14]), "+f"(d[15]),
     "+f"(d[16]), "+f"(d[17]), "+f"(d[18]), "+f"(d[19]), "+f"(d[20]), "+f"(d[21]), "+f"(d[22]), "+f"(d[23]),
     "+f"(d[24]), "+f"(d[25]), "+f"(d[26]), "+f"(d[27]), "+f"(d[28]), "+f"(d[29]), "+f"(d[30]), "+f"(d[31])
   : "l"(da), "l"(db), "r"(sd), "n"(TA), "n"(TB));
}
template<int TA, int TB> __device__ __forceinline__ void wgmma_ss_n96(float (&d)[48], uint64_t da, uint64_t db, int sd) {
  asm volatile("{\n.reg .pred p;\nsetp.ne.b32 p, %50, 0;\n"
   "wgmma.mma_async.sync.aligned.m64n96k16.f32.bf16.bf16 {"
   "%0, %1, %2, %3, %4, %5, %6, %7, %8, %9, %10, %11, %12, %13, %14, %15, "
   "%16, %17, %18, %19, %20, %21, %22, %23, %24, %25, %26, %27, %28, %29, %30, %31, "
   "%32, %33, %34, %35, %36, %37, %38, %39, %40, %41, %42, %43, %44, %45, %46, %47"
   "}, %48, %49, p, 1, 1, %51, %52;\n}\n"
   : "+f"(d[0]), "+f"(d[1]), "+f"(d[2]), "+f"(d[3]), "+f"(d[4]), "+f"(d[5]), "+f"(d[6]), "+f"(d[7]),
     "+f"(d[8]), "+f"(d[9]), "+f"(d[10]), "+f"(d[11]), "+f"(d[12]), "+f"(d[13]), "+f"(d[14]), "+f"(d[15]),
     "+f"(d[16]), "+f"(d[17]), "+f"(d[18]), "+f"(d[19]), "+f"(d[20]), "+f"(d[21]), "+f"(d[22]), "+f"(d[23]),
     "+f"(d[24]), "+f"(d[25]), "+f"(d[26]), "+f"(d[27]), "+f"(d[28]), "+f"(d[29]), "+f"(d[30]), "+f"(d[31]),
     "+f"(d[32]), "+f"(d[33]), "+f"(d[34]), "+f"(d[35]), "+f"(d[36]), "+f"(d[37]), "+f"(d[38]), "+f"(d[39]),
     "+f"(d[40]), "+f"(d[41]), "+f"(d[42]), "+f"(d[43]), "+f"(d[44]), "+f"(d[45]), "+f"(d[46]), "+f"(d[47])
   : "l"(da), "l"(db), "r"(sd), "n"(TA), "n"(TB));
}
template<int TB> __device__ __forceinline__ void wgmma_rs_n24(float (&d)[12], uint32_t a0, uint32_t a1, uint32_t a2, uint32_t a3, uint64_t db, int sd) {
  asm volatile("{\n.reg .pred p;\nsetp.ne.b32 p, %17, 0;\n"
   "wgmma.mma_async.sync.aligned.m64n24k16.f32.bf16.bf16 {"
   "%0, %1, %2, %3, %4, %5, %6, %7, %8, %9, %10, %11"
   "}, {%12, %13, %14, %15}, %16, p, 1, 1, %18;\n}\n"
   : "+f"(d[0]), "+f"(d[1]), "+f"(d[2]), "+f"(d[3]), "+f"(d[4]), "+f"(d[5]), "+f"(d[6]), "+f"(d[7]),
     "+f"(d[8]), "+f"(d[9]), "+f"(d[10]), "+f"(d[11])
   : "r"(a0), "r"(a1), "r"(a2), "r"(a3), "l"(db), "r"(sd), "n"(TB));
}
template<int TB> __device__ __forceinline__ void wgmma_rs_n32(float (&d)[16], uint32_t a0, uint32_t a1, uint32_t a2, uint32_t a3, uint64_t db, int sd) {
  asm volatile("{\n.reg .pred p;\nsetp.ne.b32 p, %21, 0;\n"
   "wgmma.mma_async.sync.aligned.m64n32k16.f32.bf16.bf16 {"
   "%0, %1, %2, %3, %4, %5, %6, %7, %8, %9, %10, %11, %12, %13, %14, %15"
   "}, {%16, %17, %18, %19}, %20, p, 1, 1, %22;\n}\n"
   : "+f"(d[0]), "+f"(d[1]), "+f"(d[2]), "+f"(d[3]), "+f"(d[4]), "+f"(d[5]), "+f"(d[6]), "+f"(d[7]),
     "+f"(d[8]), "+f"(d[9]), "+f"(d[10]), "+f"(d[11]), "+f"(d[12]), "+f"(d[13]), "+f"(d[14]), "+f"(d[15])
   : "r"(a0), "r"(a1), "r"(a2), "r"(a3), "l"(db), "r"(sd), "n"(TB));
}
template<int TB> __device__ __forceinline__ void wgmma_rs_n224(float (&d)[112], uint32_t a0, uint32_t a1, uint32_t a2, uint32_t a3, uint64_t db, int sd) {
  asm volatile("{\n.reg .pred p;\nsetp.ne.b32 p, %117, 0;\n"
   "wgmma.mma_async.sync.aligned.m64n224k16.f32.bf16.bf16 {"
   "%0, %1, %2, %3, %4, %5, %6, %7, %8, %9, %10, %11, %12, %13, %14, %15, "
   "%16, %17, %18, %19, %20, %21, %22, %23, %24, %25, %26, %27, %28, %29, %30, %31, "
   "%32, %33, %34, %35, %36, %37, %38, %39, %40, %41, %42, %43, %44, %45, %46, %47, "
   "%48, %49, %50, %51, %52, %53, %54, %55, %56, %57, %58, %59, %60, %61, %62, %63, "
   "%64, %65, %66, %67, %68, %69, %70, %71, %72, %73, %74, %75, %76, %77, %78, %79, "
   "%80, %81, %82, %83, %84, %85, %86, %87, %88, %89, %90, %91, %92, %93, %94, %95, "
   "%96, %97, %98, %99, %100, %101, %102, %103, %104, %105, %106, %107, %108, %109, %110, %111"
   "}, {%112, %113, %114, %115}, %116, p, 1, 1, %118;\n}\n"
   : "+f"(d[0]), "+f"(d[1]), "+f"(d[2]), "+f"(d[3]), "+f"(d[4]), "+f"(d[5]), "+f"(d[6]), "+f"(d[7]),
     "+f"(d[8]), "+f"(d[9]), "+f"(d[10]), "+f"(d[11]), "+f"(d[12]), "+f"(d[13]), "+f"(d[14]), "+f"(d[15]),
     "+f"(d[16]), "+f"(d[17]), "+f"(d[18]), "+f"(d[19]), "+f"(d[20]), "+f"(d[21]), "+f"(d[22]), "+f"(d[23]),
     "+f"(d[24]), "+f"(d[25]), "+f"(d[26]), "+f"(d[27]), "+f"(d[28]), "+f"(d[29]), "+f"(d[30]), "+f"(d[31]),
     "+f"(d[32]), "+f"(d[33]), "+f"(d[34]), "+f"(d[35]), "+f"(d[36]), "+f"(d[37]), "+f"(d[38]), "+f"(d[39]),
     "+f"(d[40]), "+f"(d[41]), "+f"(d[42]), "+f"(d[43]), "+f"(d[44]), "+f"(d[45]), "+f"(d[46]), "+f"(d[47]),
     "+f"(d[48]), "+f"(d[49]), "+f"(d[50]), "+f"(d[51]), "+f"(d[52]), "+f"(d[53]), "+f"(d[54]), "+f"(d[55]),
     "+f"(d[56]), "+f"(d[57]), "+f"(d[58]), "+f"(d[59]), "+f"(d[60]), "+f"(d[61]), "+f"(d[62]), "+f"(d[63]),
     "+f"(d[64]), "+f"(d[65]), "+f"(d[66]), "+f"(d[67]), "+f"(d[68]), "+f"(d[69]), "+f"(d[70]), "+f"(d[71]),
     "+f"(d[72]), "+f"(d[73]), "+f"(d[74]), "+f"(d[75]), "+f"(d[76]), "+f"(d[77]), "+f"(d[78]), "+f"(d[79]),
     "+f"(d[80]), "+f"(d[81]), "+f"(d[82]), "+f"(d[83]), "+f"(d[84]), "+f"(d[85]), "+f"(d[86]), "+f"(d[87]),
     "+f"(d[88]), "+f"(d[89]), "+f"(d[90]), "+f"(d[91]), "+f"(d[92]), "+f"(d[93]), "+f"(d[94]), "+f"(d[95]),
     "+f"(d[96]), "+f"(d[97]), "+f"(d[98]), "+f"(d[99]), "+f"(d[100]), "+f"(d[101]), "+f"(d[102]), "+f"(d[103]),
     "+f"(d[104]), "+f"(d[105]), "+f"(d[106]), "+f"(d[107]), "+f"(d[108]), "+f"(d[109]), "+f"(d[110]), "+f"(d[111])
   : "r"(a0), "r"(a1), "r"(a2), "r"(a3), "l"(db), "r"(sd), "n"(TB));
}
template<int TB> __device__ __forceinline__ void wgmma_rs_n232(float (&d)[116], uint32_t a0, uint32_t a1, uint32_t a2, uint32_t a3, uint64_t db, int sd) {
  asm volatile("{\n.reg .pred p;\nsetp.ne.b32 p, %121, 0;\n"
   "wgmma.mma_async.sync.aligned.m64n232k16.f32.bf16.bf16 {"
   "%0, %1, %2, %3, %4, %5, %6, %7, %8, %9, %10, %11, %12, %13, %14, %15, "
   "%16, %17, %18, %19, %20, %21, %22, %23, %24, %25, %26, %27, %28, %29, %30, %31, "
   "%32, %33, %34, %35, %36, %37, %38, %39, %40, %41, %42, %43, %44, %45, %46, %47, "
   "%48, %49, %50, %51, %52, %53, %54, %55, %56, %57, %58, %59, %60, %61, %62, %63, "
   "%64, %65, %66, %67, %68, %69, %70, %71, %72, %73, %74, %75, %76, %77, %78, %79, "
   "%80, %81, %82, %83, %84, %85, %86, %87, %88, %89, %90, %91, %92, %93, %94, %95, "
   "%96, %97, %98, %99, %100, %101, %102, %103, %104, %105, %106, %107, %108, %109, %110, %111, "
   "%112, %113, %114, %115"
   "}, {%116, %117, %118, %119}, %120, p, 1, 1, %122;\n}\n"
   : "+f"(d[0]), "+f"(d[1]), "+f"(d[2]), "+f"(d[3]), "+f"(d[4]), "+f"(d[5]), "+f"(d[6]), "+f"(d[7]),
     "+f"(d[8]), "+f"(d[9]), "+f"(d[10]), "+f"(d[11]), "+f"(d[12]), "+f"(d[13]), "+f"(d[14]), "+f"(d[15]),
     "+f"(d[16]), "+f"(d[17]), "+f"(d[18]), "+f"(d[19]), "+f"(d[20]), "+f"(d[21]), "+f"(d[22]), "+f"(d[23]),
     "+f"(d[24]), "+f"(d[25]), "+f"(d[26]), "+f"(d[27]), "+f"(d[28]), "+f"(d[29]), "+f"(d[30]), "+f"(d[31]),
     "+f"(d[32]), "+f"(d[33]), "+f"(d[34]), "+f"(d[35]), "+f"(d[36]), "+f"(d[37]), "+f"(d[38]), "+f"(d[39]),
     "+f"(d[40]), "+f"(d[41]), "+f"(d[42]), "+f"(d[43]), "+f"(d[44]), "+f"(d[45]), "+f"(d[46]), "+f"(d[47]),
     "+f"(d[48]), "+f"(d[49]), "+f"(d[50]), "+f"(d[51]), "+f"(d[52]), "+f"(d[53]), "+f"(d[54]), "+f"(d[55]),
     "+f"(d[56]), "+f"(d[57]), "+f"(d[58]), "+f"(d[59]), "+f"(d[60]), "+f"(d[61]), "+f"(d[62]), "+f"(d[63]),
     "+f"(d[64]), "+f"(d[65]), "+f"(d[66]), "+f"(d[67]), "+f"(d[68]), "+f"(d[69]), "+f"(d[70]), "+f"(d[71]),
     "+f"(d[72]), "+f"(d[73]), "+f"(d[74]), "+f"(d[75]), "+f"(d[76]), "+f"(d[77]), "+f"(d[78]), "+f"(d[79]),
     "+f"(d[80]), "+f"(d[81]), "+f"(d[82]), "+f"(d[83]), "+f"(d[84]), "+f"(d[85]), "+f"(d[86]), "+f"(d[87]),
     "+f"(d[88]), "+f"(d[89]), "+f"(d[90]), "+f"(d[91]), "+f"(d[92]), "+f"(d[93]), "+f"(d[94]), "+f"(d[95]),
     "+f"(d[96]), "+f"(d[97]), "+f"(d[98]), "+f"(d[99]), "+f"(d[100]), "+f"(d[101]), "+f"(d[102]), "+f"(d[103]),
     "+f"(d[104]), "+f"(d[105]), "+f"(d[106]), "+f"(d[107]), "+f"(d[108]), "+f"(d[109]), "+f"(d[110]), "+f"(d[111]),
     "+f"(d[112]), "+f"(d[113]), "+f"(d[114]), "+f"(d[115])
   : "r"(a0), "r"(a1), "r"(a2), "r"(a3), "l"(db), "r"(sd), "n"(TB));
}

__device__ __forceinline__ void mbar_init(uint32_t a, uint32_t c) { asm volatile("mbarrier.init.shared::cta.b64 [%0], %1;" ::"r"(a), "r"(c) : "memory"); }
__device__ __forceinline__ void mbar_expect_tx(uint32_t a, uint32_t b) { asm volatile("mbarrier.arrive.expect_tx.shared::cta.b64 _, [%0], %1;" ::"r"(a), "r"(b) : "memory"); }
__device__ __forceinline__ void mbar_arrive(uint32_t a) { asm volatile("mbarrier.arrive.shared::cta.b64 _, [%0];" ::"r"(a) : "memory"); }
__device__ __forceinline__ void mbar_wait(uint32_t a, uint32_t p) {
  asm volatile("{\n.reg .pred P1;\n.reg .u32 c;\nmov.u32 c, 0;\nWAIT_LOOP:\n"
               "mbarrier.try_wait.parity.shared::cta.b64 P1, [%0], %1;\n@P1 bra DONE;\n"
               "add.u32 c, c, 1;\nsetp.lt.u32 P1, c, 4000000;\n@P1 bra WAIT_LOOP;\ntrap;\nDONE:\n}" ::"r"(a), "r"(p) : "memory");
}
__device__ __forceinline__ void tma3d(uint32_t dst, const CUtensorMap* map, int c1, int c2, uint32_t bar) {
  asm volatile("cp.async.bulk.tensor.3d.shared::cluster.global.mbarrier::complete_tx::bytes [%0], [%1, {%2, %3, %4}], [%5];"
               ::"r"(dst), "l"(map), "r"(0), "r"(c1), "r"(c2), "r"(bar) : "memory");
}
__device__ __forceinline__ uint32_t desc_lo(uint32_t addr, uint32_t lbo) { return ((addr & 0x3FFFF) >> 4) | ((lbo >> 4) << 16); }
__device__ __forceinline__ uint64_t desc_mk(uint32_t lo) { uint64_t d; asm("mov.b64 %0, {%1, %2};" : "=l"(d) : "r"(lo), "r"(0x40000040)); return d; }
#define WG_FENCE() asm volatile("wgmma.fence.sync.aligned;" ::: "memory")
#define WG_COMMIT() asm volatile("wgmma.commit_group.sync.aligned;" ::: "memory")
#define WG_WAIT(n) asm volatile("wgmma.wait_group.sync.aligned %0;" ::"n"(n) : "memory")
template <int N> __device__ __forceinline__ void fop(float (&d)[N]) {
#pragma unroll
  for (int i = 0; i < N; i++) asm volatile("" : "+f"(d[i])::"memory");
}
__device__ __forceinline__ uint32_t pack(float a, float b) { uint32_t r; asm("cvt.rn.bf16x2.f32 %0, %1, %2;" : "=r"(r) : "f"(b), "f"(a)); return r; }
__device__ __forceinline__ float ex2(float x) { float y; asm("ex2.approx.ftz.f32 %0, %1;" : "=f"(y) : "f"(x)); return y; }
__device__ __forceinline__ void nb_sync(int id, int n) { asm volatile("bar.sync %0, %1;" ::"r"(id), "r"(n) : "memory"); }
__device__ __forceinline__ void nb_arrive(int id, int n) { asm volatile("bar.arrive %0, %1;" ::"r"(id), "r"(n) : "memory"); }
__device__ __forceinline__ bool elect() { uint32_t p; asm volatile("{\n.reg .pred P;\nelect.sync _|P, 0xffffffff;\nselp.u32 %0,1,0,P;\n}" : "=r"(p)); return p; }
__device__ __forceinline__ void stsm4(uint32_t a, uint32_t r0, uint32_t r1, uint32_t r2, uint32_t r3) {
  asm volatile("stmatrix.sync.aligned.m8n8.x4.shared.b16 [%0], {%1,%2,%3,%4};" ::"r"(a), "r"(r0), "r"(r1), "r"(r2), "r"(r3) : "memory");
}
__device__ __forceinline__ void stsm4t(uint32_t a, uint32_t r0, uint32_t r1, uint32_t r2, uint32_t r3) {
  asm volatile("stmatrix.sync.aligned.m8n8.x4.trans.shared.b16 [%0], {%1,%2,%3,%4};" ::"r"(a), "r"(r0), "r"(r1), "r"(r2), "r"(r3) : "memory");
}
__device__ __forceinline__ void l2_pull(uint32_t dump, const void* g) {
  asm volatile("cp.async.ca.shared.global.L2::256B [%0], [%1], 4;" ::"r"(dump), "l"(g) : "memory");
}
__device__ __forceinline__ void proxy_fence() { asm volatile("fence.proxy.async.shared::cta;" ::: "memory"); }
__device__ __forceinline__ float bf_lo(uint32_t v) { return __uint_as_float(v << 16); }
__device__ __forceinline__ float bf_hi(uint32_t v) { return __uint_as_float(v & 0xffff0000u); }

template <int V> struct IC { static constexpr int value = V; };

#define CLUSTER
__global__ void CLUSTER __launch_bounds__(384, 1)
gqa_fused_kernel(const __grid_constant__ Params prm, __nv_bfloat16* __restrict__ out, uint32_t zero) {
  extern __shared__ __align__(1024) char smem[];
  const uint32_t sb = (uint32_t)__cvta_generic_to_shared(smem);
  const uint32_t qfull = sb + OFF_BAR, accrdy = qfull + 32, tagp = qfull + 40, xfull = qfull + 64, wofull = qfull + 128, kvfull = qfull + 384;
  const int warp = __shfl_sync(0xffffffff, threadIdx.x >> 5, 0);
  const int wg = warp >> 2, wiw = warp & 3, lane = threadIdx.x & 31;
  const int kvh = (blockIdx.x >> 1) & 7, bb = ((blockIdx.x >> 4) & 3) * 2 + (blockIdx.x & 1), blk = blockIdx.x >> 6, grp = blk * 8 + bb;
  const CUtensorMap* maps = prm.m + blk * 7;
  const int kvrow0 = (bb * 8 + kvh) * SK;

  auto issue_wq = [&](int d) {
    const uint32_t bar = qfull + 8 * (d & 3);
    mbar_expect_tx(bar, 2 * SLOT);
    tma3d(sb + OFF_RING + ((d + 2) & 3) * 2 * SLOT, maps + 3, d * 32, kvh * 8, bar);
  };
  auto issue_kv = [&](int i, int slot) {
    const uint32_t bar = kvfull + 8 * i;
    mbar_expect_tx(bar, i < 2 ? 8192 : KVS);
    asm volatile("cp.async.bulk.tensor.3d.shared::cluster.global.mbarrier::complete_tx::bytes.L2::cache_hint [%0], [%1, {%2, %3, %4}], [%5], %6;"
                 ::"r"(sb + OFF_RING + slot * KVS), "l"(maps + (i < 2 ? 5 : 1) + (i & 1)), "r"(0), "r"(kvrow0 + (i < 2 ? 0 : (i >> 1) * 48 - 32)), "r"(0), "r"(bar),
                   "l"(0x12F0000000000000ull) : "memory");
  };
  auto issue_wo = [&](int w) {
    const int p = w >> 2; int t = p + kvh + 1; if (kvh == 7) t = p; else if (t >= 7) t -= 7;
    const uint32_t bar = wofull + 8 * w;
    mbar_expect_tx(bar, SLOT);
    tma3d(sb + OFF_RING + ((w + 6) & 7) * SLOT, maps + 4, kvh * 512 + (w & 3) * 128, t, bar);
  };

  if (elect()) {
    if (warp == 0) {
      if (sb & 1023) __trap();
      mbar_init(qfull, 1); mbar_init(xfull, 1);
      issue_wq(0);
      mbar_expect_tx(xfull, XCH); tma3d(sb, maps, bb * SQ, 0, xfull);
    } else if (warp == 1) {
#pragma unroll
      for (int i = 1; i < 4; i++) mbar_init(qfull + 8 * i, 1);
    } else if (warp == 2) {
#pragma unroll
      for (int c = 1; c < 7; c++) mbar_init(xfull + 8 * c, 1);
    }
  }
  __syncthreads();
  if (warp == 2 && elect()) {
    issue_wq(1);
    mbar_expect_tx(xfull + 8, XCH); tma3d(sb + XCH, maps, bb * SQ, 1, xfull + 8);
    issue_wq(2); issue_wq(3);
    for (int c = 2; c < 7; c++) { mbar_expect_tx(xfull + 8 * c, XCH); tma3d(sb + c * XCH, maps, bb * SQ, c, xfull + 8 * c); }
  }
  if (warp >= 4 && elect()) {
    if (warp < 8) {
#pragma unroll
      for (int i = 0; i < 7; i++) mbar_init(wofull + 8 * ((warp - 4) * 7 + i), 1);
      if (warp == 4) mbar_init(accrdy, 4);
      if (warp == 5) { const uint32_t e = __ldcg(g_epoch + grp * 32); asm volatile("st.shared.u32 [%0], %1;" ::"r"(tagp), "r"(e) : "memory"); }
    } else {
#pragma unroll
      for (int i = 0; i < 11; i++) mbar_init(kvfull + 8 * ((warp - 8) * 11 + i), 1);
    }
    proxy_fence();
  }
  __syncwarp();
  TRACE(1);

  {
    auto kv_prefetch = [&](int d) {
      if (d == 0) {
        const int idx = threadIdx.x;
        const char* w = prm.kv[4 + blk] + kvh * 1024;
        if (idx < 320) asm volatile("prefetch.global.L2 [%0];" ::"l"(w + (size_t)(128 + (idx >> 3) * 8 + bb) * 8192 + (idx & 7) * 128) : "memory");
      }
      const int tau = 3 * (d - PF_OFF) + wg;
      const int u = (tau * PF_NUM) / PF_DEN + (3 - wiw);
      if (d >= PF_OFF && u < ((tau + 1) * PF_NUM) / PF_DEN && u < 2 * PF_N) {
        const int q0 = u >> 1;
        const int i = q0 < PF_C ? q0 : PF_C + PF_S0 + (q0 - PF_C) * PF_STR;
        l2_pull(sb + OFF_BAR + 1024 + lane * 4, prm.kv[blk * 2 + (i & 1)] + (size_t)(kvrow0 + (i >> 1) * 32) * 512 + (u & 1) * 8192 + lane * 256);
      }
    };
    const uint32_t ringlo = desc_lo(sb + OFF_RING, 2048), xlo = desc_lo(sb, 16);
    float a0[48], a1[48], a2[32], b0[16], b1[16];
    constexpr int ND = 14;
    auto duties = [&](int d) {
      if (!(wg == 2 && d == ND - 1)) nb_arrive(1 + (wg == 2 ? 0 : wg + 1), 256);
      if (warp == 9 && d >= 1) {
        if (elect()) {
          const int r = d - 1;
          if (r + 4 < ND) issue_wq(r + 4);
          else { issue_kv(r - 10, r - 10); if (r == 12) issue_kv(3, 3); }
        }
        __syncwarp();
      }
      if (warp == 1 && d + 1 < ND) {
        if (d & 1) mbar_wait(xfull + 8 * ((d + 1) >> 1), 0);
        mbar_wait(qfull + 8 * ((d + 1) & 3), ((d + 1) >> 2) & 1);
      }
      kv_prefetch(d);
    };
    if (wg == 0) { mbar_wait(xfull, 0); mbar_wait(qfull, 0); }
    if (wg < 2) {
      for (int d = 0; d < ND; d++) {
        const uint32_t alo = ringlo + ((d + 2) & 3) * (2 * SLOT >> 4), xs = xlo + (((d >> 1) * XCH + (d & 1) * 64) >> 4);
        if (d + wg > 0) nb_sync(1 + wg, 256);
        if ((d & 1) == 0) TRACEW(48 + (d >> 1), threadIdx.x == 96);
        WG_FENCE();
#pragma unroll
        for (int k = 0; k < 2; k++) {
          wgmma_ss_n96<1, 0>(a0, desc_mk(alo + wg * (8192 >> 4) + k * (2048 >> 4)), desc_mk(xs + k * 2), (d | k) != 0);
          wgmma_ss_n96<1, 0>(a1, desc_mk(alo + wg * (8192 >> 4) + ((4096 + k * 2048) >> 4)), desc_mk(xs + k * 2), (d | k) != 0);
          wgmma_ss_n64<1, 0>(a2, desc_mk(alo + (6 + wg) * (4096 >> 4) + k * (2048 >> 4)), desc_mk(xs + k * 2), (d | k) != 0);
        }
        WG_COMMIT();
        duties(d);
        WG_WAIT(0); fop(a0); fop(a1); fop(a2);
      }
    } else {
      for (int d = 0; d < ND; d++) {
        const uint32_t alo = ringlo + ((d + 2) & 3) * (2 * SLOT >> 4), xs = xlo + (((d >> 1) * XCH + (d & 1) * 64) >> 4);
        nb_sync(3, 256);
        WG_FENCE();
#pragma unroll
        for (int k = 0; k < 2; k++) {
          wgmma_ss_n96<1, 0>(a0, desc_mk(alo + ((4 * 4096 + k * 2048) >> 4)), desc_mk(xs + k * 2), (d | k) != 0);
          wgmma_ss_n96<1, 0>(a1, desc_mk(alo + ((5 * 4096 + k * 2048) >> 4)), desc_mk(xs + k * 2), (d | k) != 0);
          wgmma_ss_n32<1, 0>(b0, desc_mk(alo + ((6 * 4096 + k * 2048) >> 4)), desc_mk(xs + k * 2 + (64 * 128 >> 4)), (d | k) != 0);
          wgmma_ss_n32<1, 0>(b1, desc_mk(alo + ((7 * 4096 + k * 2048) >> 4)), desc_mk(xs + k * 2 + (64 * 128 >> 4)), (d | k) != 0);
        }
        WG_COMMIT();
        duties(d);
        WG_WAIT(0); fop(a0); fop(a1); fop(b0); fop(b1);
      }
    }
    TRACE(55);
    __syncthreads();
    TRACE(56);
    if (threadIdx.x == 288) issue_kv(4, 4);
    __syncwarp();
    {
      const int g = 2 * wiw + ((lane >> 3) & 1);
      const uint32_t base = sb + ((lane >> 4) * 8 + (lane & 7)) * 128 + ((g ^ (lane & 7)) << 4);
      const uint32_t t0 = base + (wg & 1) * 2 * QCH + (wg >> 1) * XCH;
#pragma unroll
      for (int j = 0; j < 12; j += 2) {
        stsm4t(t0 + j * 1024, pack(a0[4 * j], a0[4 * j + 1]), pack(a0[4 * j + 2], a0[4 * j + 3]), pack(a0[4 * j + 4], a0[4 * j + 5]), pack(a0[4 * j + 6], a0[4 * j + 7]));
        stsm4t(t0 + QCH + j * 1024, pack(a1[4 * j], a1[4 * j + 1]), pack(a1[4 * j + 2], a1[4 * j + 3]), pack(a1[4 * j + 4], a1[4 * j + 5]), pack(a1[4 * j + 6], a1[4 * j + 7]));
      }
      if (wg < 2) {
#pragma unroll
        for (int j = 0; j < 8; j += 2)
          stsm4t(base + (2 + wg) * QCH + XCH + j * 1024, pack(a2[4 * j], a2[4 * j + 1]), pack(a2[4 * j + 2], a2[4 * j + 3]), pack(a2[4 * j + 4], a2[4 * j + 5]), pack(a2[4 * j + 6], a2[4 * j + 7]));
      } else {
#pragma unroll
        for (int j = 0; j < 4; j += 2) {
          stsm4t(base + 2 * QCH + XCH + (8 + j) * 1024, pack(b0[4 * j], b0[4 * j + 1]), pack(b0[4 * j + 2], b0[4 * j + 3]), pack(b0[4 * j + 4], b0[4 * j + 5]), pack(b0[4 * j + 6], b0[4 * j + 7]));
          stsm4t(base + 3 * QCH + XCH + (8 + j) * 1024, pack(b1[4 * j], b1[4 * j + 1]), pack(b1[4 * j + 2], b1[4 * j + 3]), pack(b1[4 * j + 4], b1[4 * j + 5]), pack(b1[4 * j + 6], b1[4 * j + 7]));
        }
      }
    }
    proxy_fence();
    if (warp == 1) mbar_wait(kvfull, 0);
    __syncthreads();
  }
  TRACE(2);

  {
    const uint32_t qlo = desc_lo(sb + wg * 8192, 16);
    float o[N1 / 2], park[N2 / 2];
    float m0, m1, l0 = 0.f, l1 = 0.f;
    const float c = 0.0625f * 1.4426950408889634f;
    int ks = 0;
    auto release = [&](int i, int slot) {
      if (elect()) {
        if (i + 5 < 2 * NT) issue_kv(i + 5, slot);
        else if (i == 39) { issue_wo(0); issue_wo(1); }
        else if (i == 40) issue_wo(2);
        else if (i == 41) { issue_wo(3); issue_wo(4); }
        else issue_wo(5);
      }
      __syncwarp();
    };
    auto step = [&](auto nc, int it) {
      constexpr int N = decltype(nc)::value;
      constexpr bool FIRST = (N == 16);
      float s[N / 2];
      const int vs = ks == 4 ? 0 : ks + 1;
      const uint32_t klo = desc_lo(sb + OFF_RING, 16) + ks * (KVS >> 4);
      if (!(FIRST && wg == 0)) nb_sync(1 + wg, 256);
      WG_FENCE();
#pragma unroll
      for (int kk = 0; kk < 16; kk++) {
        const uint64_t da = desc_mk(qlo + (((kk >> 2) * QCH + (kk & 3) * 32) >> 4)), db = desc_mk(klo + (((kk >> 2) * N * 128 + (kk & 3) * 32) >> 4));
        if constexpr (FIRST) wgmma_ss_n16<0, 0>(s, da, db, kk > 0); else wgmma_ss_n48<0, 0>(s, da, db, kk > 0);
      }
      WG_COMMIT();
      if (FIRST && wg == 0) nb_arrive(2, 256); else nb_arrive(4 + (wg == 0 ? 2 : wg - 1), 256);
      if (!FIRST && warp == 9) release(2 * it - 1, ks == 0 ? 4 : ks - 1);
      if (warp == 1) mbar_wait(kvfull + 8 * (2 * it + 1), 0);
      WG_WAIT(0); fop(s);
      float n0 = fmaxf(s[0], s[1]), n1 = fmaxf(s[2], s[3]);
#pragma unroll
      for (int i = 4; i < N / 2; i += 4) { n0 = fmaxf(n0, fmaxf(s[i], s[i + 1])); n1 = fmaxf(n1, fmaxf(s[i + 2], s[i + 3])); }
      n0 *= c; n1 *= c;
      if (FIRST || __any_sync(0xffffffffu, fmaxf(n0 - m0, n1 - m1) > 8.f)) {
        if (!FIRST) { n0 = fmaxf(n0, m0); n1 = fmaxf(n1, m1); }
        n0 = fmaxf(n0, __shfl_xor_sync(0xffffffffu, n0, 1)); n1 = fmaxf(n1, __shfl_xor_sync(0xffffffffu, n1, 1));
        n0 = fmaxf(n0, __shfl_xor_sync(0xffffffffu, n0, 2)); n1 = fmaxf(n1, __shfl_xor_sync(0xffffffffu, n1, 2));
        if (!FIRST) {
          const float a0 = ex2(m0 - n0), a1 = ex2(m1 - n1);
          l0 *= a0; l1 *= a1;
#pragma unroll
          for (int i = 0; i < N1 / 2; i += 4) { o[i] *= a0; o[i + 1] *= a0; o[i + 2] *= a1; o[i + 3] *= a1; }
#pragma unroll
          for (int i = 0; i < N2 / 2; i += 4) { park[i] *= a0; park[i + 1] *= a0; park[i + 2] *= a1; park[i + 3] *= a1; }
        }
        m0 = n0; m1 = n1;
      }
      uint32_t p[N / 4];
#pragma unroll
      for (int i = N / 2 - 4; i >= 0; i -= 4) {
        const float e0 = ex2(fmaf(s[i], c, -m0)), e1 = ex2(fmaf(s[i + 1], c, -m0)), e2 = ex2(fmaf(s[i + 2], c, -m1)), e3 = ex2(fmaf(s[i + 3], c, -m1));
        l0 += e0 + e1; l1 += e2 + e3;
        p[i / 2] = pack(e0, e1); p[i / 2 + 1] = pack(e2, e3);
      }
      if (!FIRST) fop(o);
      const uint32_t vlo = desc_lo(sb + OFF_RING, N * 128) + vs * (KVS >> 4);
      nb_sync(4 + wg + ((__float_as_uint(l0) | __float_as_uint(l1)) & zero), 256);
      float o2[N2 / 2];
      WG_FENCE();
#pragma unroll
      for (int kk = 0; kk < N / 16; kk++) {
        const uint64_t db = desc_mk(vlo + ((kk * 2048) >> 4)), db2 = desc_mk(vlo + ((kk * 2048 + 3 * N * 128 + (N1 - 192) * 2) >> 4));
        wgmma_rs_n224<1>(o, p[kk * 4], p[kk * 4 + 1], p[kk * 4 + 2], p[kk * 4 + 3], db, !FIRST);
        wgmma_rs_n32<1>(o2, p[kk * 4], p[kk * 4 + 1], p[kk * 4 + 2], p[kk * 4 + 3], db2, kk);
      }
      WG_COMMIT();
      if (wg == 0 || it < NT - 1) nb_arrive(1 + (wg == 0 ? 2 : wg - 1), 256);
      else if (wg == 1) nb_arrive(6, 256);
      if (warp == 9) release(2 * it, ks);
      if (warp == 1 && it + 1 < NT) mbar_wait(kvfull + 8 * (2 * it + 2), 0);
      ks = vs == 4 ? 0 : vs + 1;
      if ((it & 3) == 0) TRACEW(57 + (it >> 2), threadIdx.x == 192);
      WG_WAIT(0); fop(o); fop(o2);
#pragma unroll
      for (int i = 0; i < N2 / 2; i++) { if (FIRST) asm volatile("mov.b32 %0, %1;" : "=f"(park[i]) : "f"(o2[i])); else park[i] += o2[i]; }
    };
    step(IC<16>(), 0);
#pragma unroll 1
    for (int it = 1; it < NT; it++) step(IC<48>(), it);
    TRACE(3); TRACEW(6, threadIdx.x == 256);
    l0 += __shfl_xor_sync(0xffffffffu, l0, 1); l1 += __shfl_xor_sync(0xffffffffu, l1, 1);
    l0 += __shfl_xor_sync(0xffffffffu, l0, 2); l1 += __shfl_xor_sync(0xffffffffu, l1, 2);
    const float r0 = 1.f / l0, r1 = 1.f / l1;
    const uint32_t base = sb + (wg * 64 + wiw * 16 + (lane & 7) + ((lane >> 3) & 1) * 8) * 128;
#pragma unroll
    for (int j = 0; j < 32; j += 2) {
      float v[8];
#pragma unroll
      for (int i = 0; i < 8; i++) { const int q = 4 * j + i; v[i] = (q < N1 / 2 ? o[q < N1 / 2 ? q : 0] : park[q >= N1 / 2 ? q - N1 / 2 : 0]) * ((i & 2) ? r1 : r0); }
      const int g = j + (lane >> 4);
      stsm4(base + (j >> 3) * QCH + (((g & 7) ^ (lane & 7)) << 4), pack(v[0], v[1]), pack(v[2], v[3]), pack(v[4], v[5]), pack(v[6], v[7]));
    }
    proxy_fence();
    __syncthreads();
    if (threadIdx.x == 256) { issue_wo(6); issue_wo(7); }
    __syncwarp();
  }
  TRACE(4);

  {
    const int tw = threadIdx.x & 127;
    uint32_t epoch;
    asm volatile("ld.shared.u32 %0, [%1];" : "=r"(epoch) : "r"(tagp));
    const uint32_t tag = (epoch + 1) & 1;
    const uint32_t hand = sb + OFF_RING + 2 * SLOT;
    if (wg < 2) {
      const uint32_t alo = desc_lo(sb + OFF_RING, 2048), olo = desc_lo(sb, 16);
      for (int p = wg; p < 7; p += 2) {
        float acc[48];
        const int L0 = 4 * p;
        mbar_wait(wofull + 8 * L0, 0);
        mbar_wait(wofull + 8 * (L0 + 1), 0);
        if (p > 0) nb_sync(1 + wg, 256);
        TRACEW(8 + p, tw == 0);
#pragma unroll
        for (int q = 0; q < 4; q++) {
          const int L = L0 + q;
          WG_FENCE();
#pragma unroll
          for (int ks = 0; ks < 8; ks++)
            wgmma_ss_n96<1, 0>(acc, desc_mk(alo + ((L + 6) & 7) * (SLOT >> 4) + ks * (2048 >> 4)),
                               desc_mk(olo + (((2 * (q & 1) + (ks >> 2)) * QCH + (q >> 1) * XCH + (ks & 3) * 32) >> 4)), (q | ks) != 0);
          WG_COMMIT();
          if (q == 3 && p < 6) nb_arrive(2 - wg, 256);
          if (q > 0) { WG_WAIT(1); if (p < 5) nb_arrive(4 + ((L - 1) & 7), 160); }
          if (q == 1 || q == 2) mbar_wait(wofull + 8 * (L + 1), 0);
        }
        WG_WAIT(0); fop(acc);
        if (p < 5) nb_arrive(4 + ((L0 + 3) & 7), 160);
        TRACEW(24 + p, tw == 0);
        if (p < 6 || kvh == 7) {
          int t = p + kvh + 1; if (kvh == 7) t = p; else if (t >= 7) t -= 7;
          uint4* pp = g_part + ((grp * 7 + t) * 8 + kvh) * 768 + tw;
#pragma unroll
          for (int i = 0; i < 6; i++) {
            const uint32_t x = (pack(acc[8 * i], acc[8 * i + 1]) & ~1u) | tag, y = pack(acc[8 * i + 2], acc[8 * i + 3]);
            const uint32_t z = (pack(acc[8 * i + 4], acc[8 * i + 5]) & ~1u) | tag, w = pack(acc[8 * i + 6], acc[8 * i + 7]);
            asm volatile("st.relaxed.gpu.global.v2.b64 [%0], {%1,%2};" ::"l"(pp + i * 128), "l"((uint64_t)x | ((uint64_t)y << 32)), "l"((uint64_t)z | ((uint64_t)w << 32)) : "memory");
          }
          TRACEW(32 + p, tw == 0);
        } else {
#pragma unroll
          for (int i = 0; i < 12; i++)
            asm volatile("st.shared.v4.f32 [%0], {%1,%2,%3,%4};" ::"r"(hand + (i * 128 + tw) * 16),
                         "f"(acc[4 * i]), "f"(acc[4 * i + 1]), "f"(acc[4 * i + 2]), "f"(acc[4 * i + 3]) : "memory");
          __syncwarp();
          if (elect()) mbar_arrive(accrdy);
        }
      }
    } else if (wiw == 0) {
      for (int L = 0; L + 8 < NWO; L++) {
        nb_sync(4 + (L & 7), 160);
        if (elect()) issue_wo(L + 8);
        __syncwarp();
      }
    } else if (kvh != 7) {
      const int f = wiw - 1;
      const uint4* gsrc = g_part + (grp * 7 + kvh) * 8 * 768 + f * 256 + lane;
      const uint32_t hu = hand + f * 8192;
      float sum[64];
#pragma unroll
      for (int i = 0; i < 64; i++) sum[i] = 0.f;
      uint32_t pend = 0xffu;
      const uint32_t ownbit = 1u << kvh;
      auto ld_part = [&](uint4 (&v)[8], int sidx) {
#pragma unroll
        for (int i = 0; i < 8; i++) {
          uint64_t a, b;
          asm volatile("ld.relaxed.gpu.global.v2.b64 {%0,%1}, [%2];" : "=l"(a), "=l"(b) : "l"(gsrc + sidx * 768 + i * 32) : "memory");
          v[i] = make_uint4((uint32_t)a, (uint32_t)(a >> 32), (uint32_t)b, (uint32_t)(b >> 32));
        }
      };
      auto add_part = [&](const uint4 (&v)[8], int sidx) {
        uint32_t bad = 0;
#pragma unroll
        for (int i = 0; i < 8; i++) bad |= (v[i].x ^ tag) | (v[i].z ^ tag);
        if (!__any_sync(0xffffffffu, bad & 1)) {
#pragma unroll
          for (int i = 0; i < 8; i++) {
            sum[8 * i] += bf_lo(v[i].x); sum[8 * i + 1] += bf_hi(v[i].x); sum[8 * i + 2] += bf_lo(v[i].y); sum[8 * i + 3] += bf_hi(v[i].y);
            sum[8 * i + 4] += bf_lo(v[i].z); sum[8 * i + 5] += bf_hi(v[i].z); sum[8 * i + 6] += bf_lo(v[i].w); sum[8 * i + 7] += bf_hi(v[i].w);
          }
          pend &= ~(1u << sidx);
          TRACEW(16 + 7 - __popc(pend | ownbit), tw == 32);
        }
      };
      int spins = 0;
      uint32_t rdy = 0;
      while (pend) {
        const uint32_t rem = pend & ~ownbit;
        uint32_t todo = rdy & rem;
        if (__popc(rem) <= POLLMAX) todo = rem;
        const int s0 = todo ? __ffs(todo) - 1 : -1;
        todo &= todo - 1;
        const int s1 = todo ? __ffs(todo) - 1 : -1;
        uint32_t pr = ~tag;
        if (lane < 8 && (((rem & ~rdy) >> lane) & 1))
          asm volatile("ld.relaxed.gpu.global.u32 %0, [%1];" : "=r"(pr) : "l"(gsrc - lane + lane * 768 + 255) : "memory");
        uint4 v0[8], v1[8];
        if (s0 >= 0) ld_part(v0, s0);
        if (s1 >= 0) ld_part(v1, s1);
        if (pend & ownbit) {
          uint32_t ok = 1;
          if (rem == 0) mbar_wait(accrdy, 0);
          else asm volatile("{\n.reg .pred P;\nmbarrier.test_wait.parity.shared::cta.b64 P, [%1], 0;\nselp.u32 %0,1,0,P;\n}" : "=r"(ok) : "r"(accrdy) : "memory");
          if (__all_sync(0xffffffffu, ok)) {
#pragma unroll
            for (int i = 0; i < 16; i++) {
              float4 v;
              asm volatile("ld.shared.v4.f32 {%0,%1,%2,%3}, [%4];" : "=f"(v.x), "=f"(v.y), "=f"(v.z), "=f"(v.w)
                           : "r"(hu + (i >> 3) * 4096 + (i & 1) * 2048 + ((i >> 1) & 3) * 512 + lane * 16) : "memory");
              sum[4 * i] += v.x; sum[4 * i + 1] += v.y; sum[4 * i + 2] += v.z; sum[4 * i + 3] += v.w;
            }
            pend &= ~ownbit;
            TRACEW(44, tw == 32);
          }
        }
        rdy |= __ballot_sync(0xffffffffu, ((pr ^ tag) & 1) == 0);
        if (s0 >= 0) add_part(v0, s0);
        if (s1 >= 0) add_part(v1, s1);
        if (++spins > 4000000) __trap();
      }
      TRACEW(40, tw == 32);
      __syncwarp();
      const int r = (lane >> 4) * 8 + (lane & 7), h = (lane >> 3) & 1;
#pragma unroll
      for (int k = 0; k < 8; k++)
        stsm4t(hu + ((k >> 2) * 16 + r) * 128 + (((2 * (k & 3) + h) ^ (r & 7)) << 4), pack(sum[8 * k], sum[8 * k + 1]), pack(sum[8 * k + 2], sum[8 * k + 3]),
               pack(sum[8 * k + 4], sum[8 * k + 5]), pack(sum[8 * k + 6], sum[8 * k + 7]));
      __syncwarp();
      __nv_bfloat16* ob = out + (size_t)(bb * SQ + f * 32 + (lane >> 3)) * (2 * DM) + blk * DM + kvh * 64 + (lane & 7) * 8;
#pragma unroll
      for (int k = 0; k < 8; k++) {
        const int row = k * 4 + (lane >> 3);
        uint4 v;
        asm volatile("ld.shared.v4.u32 {%0,%1,%2,%3}, [%4];" : "=r"(v.x), "=r"(v.y), "=r"(v.z), "=r"(v.w) : "r"(hu + row * 128 + (((lane & 7) ^ (row & 7)) << 4)) : "memory");
        *reinterpret_cast<uint4*>(ob + (size_t)(k * 4) * (2 * DM)) = v;
      }
      TRACEW(43, tw == 32);
      if (kvh == 0 && tw == 32) g_epoch[grp * 32] = epoch + 1;
    }
  }
  TRACEW(5, threadIdx.x == (kvh == 7 ? 0 : 288)); TRACEW(7, threadIdx.x == 352);
}

typedef CUresult (*EncodeFn)(CUtensorMap*, CUtensorMapDataType, cuuint32_t, void*, const cuuint64_t*, const cuuint64_t*, const cuuint32_t*,
                             const cuuint32_t*, CUtensorMapInterleave, CUtensorMapSwizzle, CUtensorMapL2promotion, CUtensorMapFloatOOBfill);

void make_map(EncodeFn fn, CUtensorMap* m, void* ptr, uint64_t rows, uint64_t cols, uint32_t brows, uint32_t bchunks) {
  cuuint64_t dims[3] = {64, rows, cols / 64};
  cuuint64_t strides[2] = {cols * 2, 128};
  cuuint32_t box[3] = {64, brows, bchunks};
  cuuint32_t es[3] = {1, 1, 1};
  fn(m, CU_TENSOR_MAP_DATA_TYPE_BFLOAT16, 3, ptr, dims, strides, box, es, CU_TENSOR_MAP_INTERLEAVE_NONE, CU_TENSOR_MAP_SWIZZLE_128B,
     CU_TENSOR_MAP_L2_PROMOTION_L2_256B, CU_TENSOR_MAP_FLOAT_OOB_FILL_NONE);
}

}

extern "C" void kernel_launch(void* const* d_in, const int* in_sizes, int n_in, void* d_out, int out_size) {
  static EncodeFn fn = nullptr;
  if (!fn) {
    void* p = nullptr; cudaDriverEntryPointQueryResult qr;
    cudaGetDriverEntryPoint("cuTensorMapEncodeTiled", &p, cudaEnableDefault, &qr);
    fn = (EncodeFn)p;
    cudaFuncSetAttribute(gqa_fused_kernel, cudaFuncAttributeMaxDynamicSharedMemorySize, SMEM_BYTES);
  }
  Params prm;
  for (int b = 0; b < 2; b++) {
    make_map(fn, &prm.m[b * 7 + 0], d_in[b * 5 + 0], 768, 448, 96, 1);
    make_map(fn, &prm.m[b * 7 + 1], d_in[b * 5 + 1], 65536, 256, 48, 4);
    make_map(fn, &prm.m[b * 7 + 2], d_in[b * 5 + 2], 65536, 256, 48, 4);
    make_map(fn, &prm.m[b * 7 + 3], d_in[b * 5 + 3], 448, 4096, 32, 8);
    make_map(fn, &prm.m[b * 7 + 4], d_in[b * 5 + 4], 4096, 448, 128, 1);
    make_map(fn, &prm.m[b * 7 + 5], d_in[b * 5 + 1], 65536, 256, 16, 4);
    make_map(fn, &prm.m[b * 7 + 6], d_in[b * 5 + 2], 65536, 256, 16, 4);
  }
  make_map(fn, &prm.mo, d_out, 768, 896, 32, 1);
  prm.kv[0] = (const char*)d_in[1]; prm.kv[1] = (const char*)d_in[2]; prm.kv[2] = (const char*)d_in[6]; prm.kv[3] = (const char*)d_in[7]; prm.kv[4] = (const char*)d_in[3]; prm.kv[5] = (const char*)d_in[8];
  gqa_fused_kernel<<<128, 384, SMEM_BYTES, cudaStreamPerThread>>>(prm, (__nv_bfloat16*)d_out, 0u);
}
```

```cpp
#define 8.in.cu
#define PF_C 0
#define PF_DEN 2
#define PF_NUM 1
#define VLATE
#define LASTORD
#define PF_N 8
#define PF_OFF 2
#define PF_S0 9
#define PF_STR 6
#define THR_I 4
#define THR_D 32
#define THR_S 64
#define THR_7 160
#define SENDQ 2
#define THR_SPLIT
#define ON1 232
#include <cuda_runtime.h>
#include <cuda_bf16.h>
#include <cuda.h>
#include <stdint.h>

namespace {

constexpr int SQ = 96, DM = 448, SK = 1024;
constexpr int SLOT = 16384;
constexpr int KVS = 24576;
constexpr int OFF_RING = 98304;
constexpr int OFF_BAR = OFF_RING + 8 * SLOT;
constexpr int SMEM_BYTES = OFF_BAR + 1792;
constexpr int QCH = 24576;
constexpr int XCH = 12288;
constexpr int NT = 22;
constexpr int NWO = 28;
#define WARM0 0
#define THR_W 10
#define POLLMAX 0
constexpr int N1 = ON1, N2 = 256 - N1;

struct Params {
  CUtensorMap m[14];
  const char* kv[8];
};

__device__ uint4 g_part[16 * 7 * 8 * 768];
__device__ uint4 g_prog[8];
__device__ uint32_t g_epoch[16 * 32];
#define TRACEC(i, cond)
#define TRACE(i)
#define TRACEW(i, cond)

template<int TA, int TB> __device__ __forceinline__ void wgmma_ss_n16(float (&d)[8], uint64_t da, uint64_t db, int sd) {
  asm volatile("{\n.reg .pred p;\nsetp.ne.b32 p, %10, 0;\n"
   "wgmma.mma_async.sync.aligned.m64n16k16.f32.bf16.bf16 {"
   "%0, %1, %2, %3, %4, %5, %6, %7"
   "}, %8, %9, p, 1, 1, %11, %12;\n}\n"
   : "+f"(d[0]), "+f"(d[1]), "+f"(d[2]), "+f"(d[3]), "+f"(d[4]), "+f"(d[5]), "+f"(d[6]), "+f"(d[7])
   : "l"(da), "l"(db), "r"(sd), "n"(TA), "n"(TB));
}
template<int TA, int TB> __device__ __forceinline__ void wgmma_ss_n32(float (&d)[16], uint64_t da, uint64_t db, int sd) {
  asm volatile("{\n.reg .pred p;\nsetp.ne.b32 p, %18, 0;\n"
   "wgmma.mma_async.sync.aligned.m64n32k16.f32.bf16.bf16 {"
   "%0, %1, %2, %3, %4, %5, %6, %7, %8, %9, %10, %11, %12, %13, %14, %15"
   "}, %16, %17, p, 1, 1, %19, %20;\n}\n"
   : "+f"(d[0]), "+f"(d[1]), "+f"(d[2]), "+f"(d[3]), "+f"(d[4]), "+f"(d[5]), "+f"(d[6]), "+f"(d[7]),
     "+f"(d[8]), "+f"(d[9]), "+f"(d[10]), "+f"(d[11]), "+f"(d[12]), "+f"(d[13]), "+f"(d[14]), "+f"(d[15])
   : "l"(da), "l"(db), "r"(sd), "n"(TA), "n"(TB));
}
template<int TA, int TB> __device__ __forceinline__ void wgmma_ss_n48(float (&d)[24], uint64_t da, uint64_t db, int sd) {
  asm volatile("{\n.reg .pred p;\nsetp.ne.b32 p, %26, 0;\n"
   "wgmma.mma_async.sync.aligned.m64n48k16.f32.bf16.bf16 {"
   "%0, %1, %2, %3, %4, %5, %6, %7, %8, %9, %10, %11, %12, %13, %14, %15, "
   "%16, %17, %18, %19, %20, %21, %22, %23"
   "}, %24, %25, p, 1, 1, %27, %28;\n}\n"
   : "+f"(d[0]), "+f"(d[1]), "+f"(d[2]), "+f"(d[3]), "+f"(d[4]), "+f"(d[5]), "+f"(d[6]), "+f"(d[7]),
     "+f"(d[8]), "+f"(d[9]), "+f"(d[10]), "+f"(d[11]), "+f"(d[12]), "+f"(d[13]), "+f"(d[14]), "+f"(d[15]),
     "+f"(d[16]), "+f"(d[17]), "+f"(d[18]), "+f"(d[19]), "+f"(d[20]), "+f"(d[21]), "+f"(d[22]), "+f"(d[23])
   : "l"(da), "l"(db), "r"(sd), "n"(TA), "n"(TB));
}
template<int TA, int TB> __device__ __forceinline__ void wgmma_ss_n64(float (&d)[32], uint64_t da, uint64_t db, int sd) {
  asm volatile("{\n.reg .pred p;\nsetp.ne.b32 p, %34, 0;\n"
   "wgmma.mma_async.sync.aligned.m64n64k16.f32.bf16.bf16 {"
   "%0, %1, %2, %3, %4, %5, %6, %7, %8, %9, %10, %11, %12, %13, %14, %15, "
   "%16, %17, %18, %19, %20, %21, %22, %23, %24, %25, %26, %27, %28, %29, %30, %31"
   "}, %32, %33, p, 1, 1, %35, %36;\n}\n"
   : "+f"(d[0]), "+f"(d[1]), "+f"(d[2]), "+f"(d[3]), "+f"(d[4]), "+f"(d[5]), "+f"(d[6]), "+f"(d[7]),
     "+f"(d[8]), "+f"(d[9]), "+f"(d[10]), "+f"(d[11]), "+f"(d[12]), "+f"(d[13]), "+f"(d[14]), "+f"(d[15]),
     "+f"(d[16]), "+f"(d[17]), "+f"(d[18]), "+f"(d[19]), "+f"(d[20]), "+f"(d[21]), "+f"(d[22]), "+f"(d[23]),
     "+f"(d[24]), "+f"(d[25]), "+f"(d[26]), "+f"(d[27]), "+f"(d[28]), "+f"(d[29]), "+f"(d[30]), "+f"(d[31])
   : "l"(da), "l"(db), "r"(sd), "n"(TA), "n"(TB));
}
template<int TA, int TB> __device__ __forceinline__ void wgmma_ss_n96(float (&d)[48], uint64_t da, uint64_t db, int sd) {
  asm volatile("{\n.reg .pred p;\nsetp.ne.b32 p, %50, 0;\n"
   "wgmma.mma_async.sync.aligned.m64n96k16.f32.bf16.bf16 {"
   "%0, %1, %2, %3, %4, %5, %6, %7, %8, %9, %10, %11, %12, %13, %14, %15, "
   "%16, %17, %18, %19, %20, %21, %22, %23, %24, %25, %26, %27, %28, %29, %30, %31, "
   "%32, %33, %34, %35, %36, %37, %38, %39, %40, %41, %42, %43, %44, %45, %46, %47"
   "}, %48, %49, p, 1, 1, %51, %52;\n}\n"
   : "+f"(d[0]), "+f"(d[1]), "+f"(d[2]), "+f"(d[3]), "+f"(d[4]), "+f"(d[5]), "+f"(d[6]), "+f"(d[7]),
     "+f"(d[8]), "+f"(d[9]), "+f"(d[10]), "+f"(d[11]), "+f"(d[12]), "+f"(d[13]), "+f"(d[14]), "+f"(d[15]),
     "+f"(d[16]), "+f"(d[17]), "+f"(d[18]), "+f"(d[19]), "+f"(d[20]), "+f"(d[21]), "+f"(d[22]), "+f"(d[23]),
     "+f"(d[24]), "+f"(d[25]), "+f"(d[26]), "+f"(d[27]), "+f"(d[28]), "+f"(d[29]), "+f"(d[30]), "+f"(d[31]),
     "+f"(d[32]), "+f"(d[33]), "+f"(d[34]), "+f"(d[35]), "+f"(d[36]), "+f"(d[37]), "+f"(d[38]), "+f"(d[39]),
     "+f"(d[40]), "+f"(d[41]), "+f"(d[42]), "+f"(d[43]), "+f"(d[44]), "+f"(d[45]), "+f"(d[46]), "+f"(d[47])
   : "l"(da), "l"(db), "r"(sd), "n"(TA), "n"(TB));
}
template<int TB> __device__ __forceinline__ void wgmma_rs_n24(float (&d)[12], uint32_t a0, uint32_t a1, uint32_t a2, uint32_t a3, uint64_t db, int sd) {
  asm volatile("{\n.reg .pred p;\nsetp.ne.b32 p, %17, 0;\n"
   "wgmma.mma_async.sync.aligned.m64n24k16.f32.bf16.bf16 {"
   "%0, %1, %2, %3, %4, %5, %6, %7, %8, %9, %10, %11"
   "}, {%12, %13, %14, %15}, %16, p, 1, 1, %18;\n}\n"
   : "+f"(d[0]), "+f"(d[1]), "+f"(d[2]), "+f"(d[3]), "+f"(d[4]), "+f"(d[5]), "+f"(d[6]), "+f"(d[7]),
     "+f"(d[8]), "+f"(d[9]), "+f"(d[10]), "+f"(d[11])
   : "r"(a0), "r"(a1), "r"(a2), "r"(a3), "l"(db), "r"(sd), "n"(TB));
}
template<int TB> __device__ __forceinline__ void wgmma_rs_n32(float (&d)[16], uint32_t a0, uint32_t a1, uint32_t a2, uint32_t a3, uint64_t db, int sd) {
  asm volatile("{\n.reg .pred p;\nsetp.ne.b32 p, %21, 0;\n"
   "wgmma.mma_async.sync.aligned.m64n32k16.f32.bf16.bf16 {"
   "%0, %1, %2, %3, %4, %5, %6, %7, %8, %9, %10, %11, %12, %13, %14, %15"
   "}, {%16, %17, %18, %19}, %20, p, 1, 1, %22;\n}\n"
   : "+f"(d[0]), "+f"(d[1]), "+f"(d[2]), "+f"(d[3]), "+f"(d[4]), "+f"(d[5]), "+f"(d[6]), "+f"(d[7]),
     "+f"(d[8]), "+f"(d[9]), "+f"(d[10]), "+f"(d[11]), "+f"(d[12]), "+f"(d[13]), "+f"(d[14]), "+f"(d[15])
   : "r"(a0), "r"(a1), "r"(a2), "r"(a3), "l"(db), "r"(sd), "n"(TB));
}
template<int TB> __device__ __forceinline__ void wgmma_rs_n224(float (&d)[112], uint32_t a0, uint32_t a1, uint32_t a2, uint32_t a3, uint64_t db, int sd) {
  asm volatile("{\n.reg .pred p;\nsetp.ne.b32 p, %117, 0;\n"
   "wgmma.mma_async.sync.aligned.m64n224k16.f32.bf16.bf16 {"
   "%0, %1, %2, %3, %4, %5, %6, %7, %8, %9, %10, %11, %12, %13, %14, %15, "
   "%16, %17, %18, %19, %20, %21, %22, %23, %24, %25, %26, %27, %28, %29, %30, %31, "
   "%32, %33, %34, %35, %36, %37, %38, %39, %40, %41, %42, %43, %44, %45, %46, %47, "
   "%48, %49, %50, %51, %52, %53, %54, %55, %56, %57, %58, %59, %60, %61, %62, %63, "
   "%64, %65, %66, %67, %68, %69, %70, %71, %72, %73, %74, %75, %76, %77, %78, %79, "
   "%80, %81, %82, %83, %84, %85, %86, %87, %88, %89, %90, %91, %92, %93, %94, %95, "
   "%96, %97, %98, %99, %100, %101, %102, %103, %104, %105, %106, %107, %108, %109, %110, %111"
   "}, {%112, %113, %114, %115}, %116, p, 1, 1, %118;\n}\n"
   : "+f"(d[0]), "+f"(d[1]), "+f"(d[2]), "+f"(d[3]), "+f"(d[4]), "+f"(d[5]), "+f"(d[6]), "+f"(d[7]),
     "+f"(d[8]), "+f"(d[9]), "+f"(d[10]), "+f"(d[11]), "+f"(d[12]), "+f"(d[13]), "+f"(d[14]), "+f"(d[15]),
     "+f"(d[16]), "+f"(d[17]), "+f"(d[18]), "+f"(d[19]), "+f"(d[20]), "+f"(d[21]), "+f"(d[22]), "+f"(d[23]),
     "+f"(d[24]), "+f"(d[25]), "+f"(d[26]), "+f"(d[27]), "+f"(d[28]), "+f"(d[29]), "+f"(d[30]), "+f"(d[31]),
     "+f"(d[32]), "+f"(d[33]), "+f"(d[34]), "+f"(d[35]), "+f"(d[36]), "+f"(d[37]), "+f"(d[38]), "+f"(d[39]),
     "+f"(d[40]), "+f"(d[41]), "+f"(d[42]), "+f"(d[43]), "+f"(d[44]), "+f"(d[45]), "+f"(d[46]), "+f"(d[47]),
     "+f"(d[48]), "+f"(d[49]), "+f"(d[50]), "+f"(d[51]), "+f"(d[52]), "+f"(d[53]), "+f"(d[54]), "+f"(d[55]),
     "+f"(d[56]), "+f"(d[57]), "+f"(d[58]), "+f"(d[59]), "+f"(d[60]), "+f"(d[61]), "+f"(d[62]), "+f"(d[63]),
     "+f"(d[64]), "+f"(d[65]), "+f"(d[66]), "+f"(d[67]), "+f"(d[68]), "+f"(d[69]), "+f"(d[70]), "+f"(d[71]),
     "+f"(d[72]), "+f"(d[73]), "+f"(d[74]), "+f"(d[75]), "+f"(d[76]), "+f"(d[77]), "+f"(d[78]), "+f"(d[79]),
     "+f"(d[80]), "+f"(d[81]), "+f"(d[82]), "+f"(d[83]), "+f"(d[84]), "+f"(d[85]), "+f"(d[86]), "+f"(d[87]),
     "+f"(d[88]), "+f"(d[89]), "+f"(d[90]), "+f"(d[91]), "+f"(d[92]), "+f"(d[93]), "+f"(d[94]), "+f"(d[95]),
     "+f"(d[96]), "+f"(d[97]), "+f"(d[98]), "+f"(d[99]), "+f"(d[100]), "+f"(d[101]), "+f"(d[102]), "+f"(d[103]),
     "+f"(d[104]), "+f"(d[105]), "+f"(d[106]), "+f"(d[107]), "+f"(d[108]), "+f"(d[109]), "+f"(d[110]), "+f"(d[111])
   : "r"(a0), "r"(a1), "r"(a2), "r"(a3), "l"(db), "r"(sd), "n"(TB));
}
template<int TB> __device__ __forceinline__ void wgmma_rs_n232(float (&d)[116], uint32_t a0, uint32_t a1, uint32_t a2, uint32_t a3, uint64_t db, int sd) {
  asm volatile("{\n.reg .pred p;\nsetp.ne.b32 p, %121, 0;\n"
   "wgmma.mma_async.sync.aligned.m64n232k16.f32.bf16.bf16 {"
   "%0, %1, %2, %3, %4, %5, %6, %7, %8, %9, %10, %11, %12, %13, %14, %15, "
   "%16, %17, %18, %19, %20, %21, %22, %23, %24, %25, %26, %27, %28, %29, %30, %31, "
   "%32, %33, %34, %35, %36, %37, %38, %39, %40, %41, %42, %43, %44, %45, %46, %47, "
   "%48, %49, %50, %51, %52, %53, %54, %55, %56, %57, %58, %59, %60, %61, %62, %63, "
   "%64, %65, %66, %67, %68, %69, %70, %71, %72, %73, %74, %75, %76, %77, %78, %79, "
   "%80, %81, %82, %83, %84, %85, %86, %87, %88, %89, %90, %91, %92, %93, %94, %95, "
   "%96, %97, %98, %99, %100, %101, %102, %103, %104, %105, %106, %107, %108, %109, %110, %111, "
   "%112, %113, %114, %115"
   "}, {%116, %117, %118, %119}, %120, p, 1, 1, %122;\n}\n"
   : "+f"(d[0]), "+f"(d[1]), "+f"(d[2]), "+f"(d[3]), "+f"(d[4]), "+f"(d[5]), "+f"(d[6]), "+f"(d[7]),
     "+f"(d[8]), "+f"(d[9]), "+f"(d[10]), "+f"(d[11]), "+f"(d[12]), "+f"(d[13]), "+f"(d[14]), "+f"(d[15]),
     "+f"(d[16]), "+f"(d[17]), "+f"(d[18]), "+f"(d[19]), "+f"(d[20]), "+f"(d[21]), "+f"(d[22]), "+f"(d[23]),
     "+f"(d[24]), "+f"(d[25]), "+f"(d[26]), "+f"(d[27]), "+f"(d[28]), "+f"(d[29]), "+f"(d[30]), "+f"(d[31]),
     "+f"(d[32]), "+f"(d[33]), "+f"(d[34]), "+f"(d[35]), "+f"(d[36]), "+f"(d[37]), "+f"(d[38]), "+f"(d[39]),
     "+f"(d[40]), "+f"(d[41]), "+f"(d[42]), "+f"(d[43]), "+f"(d[44]), "+f"(d[45]), "+f"(d[46]), "+f"(d[47]),
     "+f"(d[48]), "+f"(d[49]), "+f"(d[50]), "+f"(d[51]), "+f"(d[52]), "+f"(d[53]), "+f"(d[54]), "+f"(d[55]),
     "+f"(d[56]), "+f"(d[57]), "+f"(d[58]), "+f"(d[59]), "+f"(d[60]), "+f"(d[61]), "+f"(d[62]), "+f"(d[63]),
     "+f"(d[64]), "+f"(d[65]), "+f"(d[66]), "+f"(d[67]), "+f"(d[68]), "+f"(d[69]), "+f"(d[70]), "+f"(d[71]),
     "+f"(d[72]), "+f"(d[73]), "+f"(d[74]), "+f"(d[75]), "+f"(d[76]), "+f"(d[77]), "+f"(d[78]), "+f"(d[79]),
     "+f"(d[80]), "+f"(d[81]), "+f"(d[82]), "+f"(d[83]), "+f"(d[84]), "+f"(d[85]), "+f"(d[86]), "+f"(d[87]),
     "+f"(d[88]), "+f"(d[89]), "+f"(d[90]), "+f"(d[91]), "+f"(d[92]), "+f"(d[93]), "+f"(d[94]), "+f"(d[95]),
     "+f"(d[96]), "+f"(d[97]), "+f"(d[98]), "+f"(d[99]), "+f"(d[100]), "+f"(d[101]), "+f"(d[102]), "+f"(d[103]),
     "+f"(d[104]), "+f"(d[105]), "+f"(d[106]), "+f"(d[107]), "+f"(d[108]), "+f"(d[109]), "+f"(d[110]), "+f"(d[111]),
     "+f"(d[112]), "+f"(d[113]), "+f"(d[114]), "+f"(d[115])
   : "r"(a0), "r"(a1), "r"(a2), "r"(a3), "l"(db), "r"(sd), "n"(TB));
}

__device__ __forceinline__ void mbar_init(uint32_t a, uint32_t c) { asm volatile("mbarrier.init.shared::cta.b64 [%0], %1;" ::"r"(a), "r"(c) : "memory"); }
__device__ __forceinline__ void mbar_expect_tx(uint32_t a, uint32_t b) { asm volatile("mbarrier.arrive.expect_tx.shared::cta.b64 _, [%0], %1;" ::"r"(a), "r"(b) : "memory"); }
__device__ __forceinline__ void mbar_arrive(uint32_t a) { asm volatile("mbarrier.arrive.shared::cta.b64 _, [%0];" ::"r"(a) : "memory"); }
__device__ __forceinline__ void mbar_wait(uint32_t a, uint32_t p) {
  asm volatile("{\n.reg .pred P1;\n.reg .u32 c;\nmov.u32 c, 0;\nWAIT_LOOP:\n"
               "mbarrier.try_wait.parity.shared::cta.b64 P1, [%0], %1;\n@P1 bra DONE;\n"
               "add.u32 c, c, 1;\nsetp.lt.u32 P1, c, 4000000;\n@P1 bra WAIT_LOOP;\ntrap;\nDONE:\n}" ::"r"(a), "r"(p) : "memory");
}
__device__ __forceinline__ void tma3d(uint32_t dst, const CUtensorMap* map, int c1, int c2, uint32_t bar) {
  asm volatile("cp.async.bulk.tensor.3d.shared::cluster.global.mbarrier::complete_tx::bytes [%0], [%1, {%2, %3, %4}], [%5];"
               ::"r"(dst), "l"(map), "r"(0), "r"(c1), "r"(c2), "r"(bar) : "memory");
}
__device__ __forceinline__ uint32_t desc_lo(uint32_t addr, uint32_t lbo) { return ((addr & 0x3FFFF) >> 4) | ((lbo >> 4) << 16); }
__device__ __forceinline__ uint64_t desc_mk(uint32_t lo) { uint64_t d; asm("mov.b64 %0, {%1, %2};" : "=l"(d) : "r"(lo), "r"(0x40000040)); return d; }
#define WG_FENCE() asm volatile("wgmma.fence.sync.aligned;" ::: "memory")
#define WG_COMMIT() asm volatile("wgmma.commit_group.sync.aligned;" ::: "memory")
#define WG_WAIT(n) asm volatile("wgmma.wait_group.sync.aligned %0;" ::"n"(n) : "memory")
template <int N> __device__ __forceinline__ void fop(float (&d)[N]) {
#pragma unroll
  for (int i = 0; i < N; i++) asm volatile("" : "+f"(d[i])::"memory");
}
__device__ __forceinline__ uint32_t pack(float a, float b) { uint32_t r; asm("cvt.rn.bf16x2.f32 %0, %1, %2;" : "=r"(r) : "f"(b), "f"(a)); return r; }
__device__ __forceinline__ float ex2(float x) { float y; asm("ex2.approx.ftz.f32 %0, %1;" : "=f"(y) : "f"(x)); return y; }
__device__ __forceinline__ void nb_sync(int id, int n) { asm volatile("bar.sync %0, %1;" ::"r"(id), "r"(n) : "memory"); }
__device__ __forceinline__ void nb_arrive(int id, int n) { asm volatile("bar.arrive %0, %1;" ::"r"(id), "r"(n) : "memory"); }
__device__ __forceinline__ bool elect() { uint32_t p; asm volatile("{\n.reg .pred P;\nelect.sync _|P, 0xffffffff;\nselp.u32 %0,1,0,P;\n}" : "=r"(p)); return p; }
__device__ __forceinline__ void stsm4(uint32_t a, uint32_t r0, uint32_t r1, uint32_t r2, uint32_t r3) {
  asm volatile("stmatrix.sync.aligned.m8n8.x4.shared.b16 [%0], {%1,%2,%3,%4};" ::"r"(a), "r"(r0), "r"(r1), "r"(r2), "r"(r3) : "memory");
}
__device__ __forceinline__ void stsm4t(uint32_t a, uint32_t r0, uint32_t r1, uint32_t r2, uint32_t r3) {
  asm volatile("stmatrix.sync.aligned.m8n8.x4.trans.shared.b16 [%0], {%1,%2,%3,%4};" ::"r"(a), "r"(r0), "r"(r1), "r"(r2), "r"(r3) : "memory");
}
__device__ __forceinline__ void l2_pull(uint32_t dump, const void* g) {
  asm volatile("cp.async.ca.shared.global.L2::256B [%0], [%1], 4;" ::"r"(dump), "l"(g) : "memory");
}
__device__ __forceinline__ void mma_add(float& d0, float& d1, float& d2, float& d3, uint32_t a0, uint32_t a1, uint32_t b, int on) {
  asm volatile("{\n.reg .pred p;\nsetp.ne.b32 p, %7, 0;\n@p mma.sync.aligned.m16n8k8.row.col.f32.bf16.bf16.f32 {%0,%1,%2,%3}, {%4,%5}, {%6}, {%0,%1,%2,%3};\n}"
               : "+f"(d0), "+f"(d1), "+f"(d2), "+f"(d3) : "r"(a0), "r"(a1), "r"(b), "r"(on));
}
__device__ __forceinline__ uint32_t set_tag(uint32_t v, uint32_t tag) { uint32_t r; asm("lop3.b32 %0, %1, 0xfffffffe, %2, 0xea;" : "=r"(r) : "r"(v), "r"(tag)); return r; }
__device__ __forceinline__ int tid_now() { int t; asm volatile("mov.u32 %0, %tid.x;" : "=r"(t)); return t; }
__device__ __forceinline__ float rcp(float x) { float y; asm("rcp.approx.ftz.f32 %0, %1;" : "=f"(y) : "f"(x)); return y; }
__device__ __forceinline__ void proxy_fence() { asm volatile("fence.proxy.async.shared::cta;" ::: "memory"); }
__device__ __forceinline__ float bf_lo(uint32_t v) { return __uint_as_float(v << 16); }
__device__ __forceinline__ float bf_hi(uint32_t v) { return __uint_as_float(v & 0xffff0000u); }

#define RDY_ID(h) ((0x540f >> (4 * (h))) & 15)
template <int V> struct IC { static constexpr int value = V; };

__global__ void __launch_bounds__(384, 1)
gqa_fused_kernel(const __grid_constant__ Params prm, __nv_bfloat16* __restrict__ out, uint32_t zero) {
  extern __shared__ __align__(1024) char smem[];
  const uint32_t sb = (uint32_t)__cvta_generic_to_shared(smem);
  const uint32_t qfull = sb + OFF_BAR, accrdy = qfull + 32, tagp = qfull + 40, xfull = qfull + 64, wofull = qfull + 128, kvfull = qfull + 384;
  const int warp = __shfl_sync(0xffffffff, threadIdx.x >> 5, 0);
  const int wg = warp >> 2, wiw = warp & 3, lane = threadIdx.x & 31;
  const int kvh = (blockIdx.x >> 1) & 7, bb = ((blockIdx.x >> 4) & 3) * 2 + (blockIdx.x & 1), blk = blockIdx.x >> 6, grp = blk * 8 + bb;
  const CUtensorMap* maps = prm.m + blk * 7;
  const int kvrow0 = (bb * 8 + kvh) * SK;

  auto issue_wq = [&](int d) {
    const uint32_t bar = qfull + 8 * (d & 3);
    mbar_expect_tx(bar, 2 * SLOT);
    tma3d(sb + OFF_RING + ((d + 2) & 3) * 2 * SLOT, maps + 3, d * 32, kvh * 8, bar);
  };
  auto issue_kv = [&](int i, int slot) {
    const uint32_t bar = kvfull + 8 * i;
    mbar_expect_tx(bar, i < 2 ? 8192 : KVS);
    asm volatile("cp.async.bulk.tensor.3d.shared::cluster.global.mbarrier::complete_tx::bytes.L2::cache_hint [%0], [%1, {%2, %3, %4}], [%5], %6;"
                 ::"r"(sb + OFF_RING + slot * KVS), "l"(maps + (i < 2 ? 5 : 1) + (i & 1)), "r"(0), "r"(kvrow0 + (i < 2 ? 0 : (i >> 1) * 48 - 32)), "r"(0), "r"(bar),
                   "l"(0x12F0000000000000ull) : "memory");
  };
  auto issue_wo = [&](int w) {
    const int p = w < 8 ? (w >> 1) & 1 : w >> 2, q = w < 8 ? (w & 1) | ((w >> 1) & 2) : w & 3;
    int t = p + kvh + 1; if (kvh == 7) t = p; else if (t >= 7) t -= 7;
    const uint32_t bar = wofull + 8 * w;
    mbar_expect_tx(bar, SLOT);
    tma3d(sb + OFF_RING + ((w + 6) & 7) * SLOT, maps + 4, kvh * 512 + q * 128, t, bar);
  };

  if (elect()) {
    if (warp == 0) {
      if (sb & 1023) __trap();
      mbar_init(qfull, 1); mbar_init(xfull, 1);
      issue_wq(0);
      mbar_expect_tx(xfull, XCH); tma3d(sb, maps, bb * SQ, 0, xfull);
    } else if (warp == 1) {
#pragma unroll
      for (int i = 1; i < 4; i++) mbar_init(qfull + 8 * i, 1);
    } else if (warp == 2) {
#pragma unroll
      for (int c = 1; c < 7; c++) mbar_init(xfull + 8 * c, 1);
    }
  }
  __syncthreads();
  if (warp == 2 && elect()) {
    issue_wq(1);
    mbar_expect_tx(xfull + 8, XCH); tma3d(sb + XCH, maps, bb * SQ, 1, xfull + 8);
    issue_wq(2); issue_wq(3);
    for (int c = 2; c < 7; c++) { mbar_expect_tx(xfull + 8 * c, XCH); tma3d(sb + c * XCH, maps, bb * SQ, c, xfull + 8 * c); }
  }
  if (warp >= 4 && elect()) {
    if (warp < 8) {
#pragma unroll
      for (int i = 0; i < 7; i++) mbar_init(wofull + 8 * ((warp - 4) * 7 + i), 1);
      if (warp == 4) mbar_init(accrdy, 4);
      if (warp == 5) { const uint32_t e = __ldcg(g_epoch + grp * 32); asm volatile("st.shared.u32 [%0], %1;" ::"r"(tagp), "r"(e) : "memory"); }
    } else {
#pragma unroll
      for (int i = 0; i < 11; i++) mbar_init(kvfull + 8 * ((warp - 8) * 11 + i), 1);
    }
    proxy_fence();
  }
  __syncwarp();
  TRACE(1);

  {
    auto kv_prefetch = [&](int d) {
      if (d == 0) {
        const int idx = threadIdx.x;
        const char* w = prm.kv[4 + blk] + kvh * 1024;
        if (idx < 320) asm volatile("prefetch.global.L2 [%0];" ::"l"(w + (size_t)(128 + (idx >> 3) * 8 + bb) * 8192 + (idx & 7) * 128) : "memory");
      }
      const int tau = 3 * (d - PF_OFF) + wg;
      const int u = (tau * PF_NUM) / PF_DEN + (3 - wiw);
      if (d >= PF_OFF && u < ((tau + 1) * PF_NUM) / PF_DEN && u < 2 * PF_N) {
        const int i = PF_S0 + (u >> 1) * PF_STR;
        l2_pull(sb + OFF_BAR + 1024 + lane * 4, prm.kv[blk * 2 + (i & 1)] + (size_t)(kvrow0 + (i >> 1) * 32) * 512 + (u & 1) * 8192 + lane * 256);
      }
    };
    const uint32_t ringlo = desc_lo(sb + OFF_RING, 2048), xlo = desc_lo(sb, 16);
    float a0[48], a1[48], a2[32], b0[16], b1[16];
    constexpr int ND = 14;
    auto duties = [&](int d) {
      if (!(wg == 2 && d == ND - 1)) nb_arrive(1 + (wg == 2 ? 0 : wg + 1), 256);
      if (warp == 9 && d >= 1) {
        if (elect()) {
          const int r = d - 1;
          if (r + 4 < ND) issue_wq(r + 4);
          else { issue_kv(r - 10, r - 10); if (r == 12) issue_kv(3, 3); }
        }
        __syncwarp();
      }
      if (warp == 1 && d + 1 < ND) {
        if (d & 1) mbar_wait(xfull + 8 * ((d + 1) >> 1), 0);
        mbar_wait(qfull + 8 * ((d + 1) & 3), ((d + 1) >> 2) & 1);
      }
      kv_prefetch(d);
    };
    if (wg == 0) { mbar_wait(xfull, 0); mbar_wait(qfull, 0); }
    if (wg < 2) {
      for (int d = 0; d < ND; d++) {
        const uint32_t alo = ringlo + ((d + 2) & 3) * (2 * SLOT >> 4), xs = xlo + (((d >> 1) * XCH + (d & 1) * 64) >> 4);
        if (d + wg > 0) nb_sync(1 + wg, 256);
        if ((d & 1) == 0) TRACEW(48 + (d >> 1), threadIdx.x == 96);
        WG_FENCE();
#pragma unroll
        for (int k = 0; k < 2; k++) {
          wgmma_ss_n96<1, 0>(a0, desc_mk(alo + wg * (8192 >> 4) + k * (2048 >> 4)), desc_mk(xs + k * 2), (d | k) != 0);
          wgmma_ss_n96<1, 0>(a1, desc_mk(alo + wg * (8192 >> 4) + ((4096 + k * 2048) >> 4)), desc_mk(xs + k * 2), (d | k) != 0);
          wgmma_ss_n64<1, 0>(a2, desc_mk(alo + (6 + wg) * (4096 >> 4) + k * (2048 >> 4)), desc_mk(xs + k * 2), (d | k) != 0);
        }
        WG_COMMIT();
        duties(d);
        WG_WAIT(0); fop(a0); fop(a1); fop(a2);
      }
    } else {
      for (int d = 0; d < ND; d++) {
        const uint32_t alo = ringlo + ((d + 2) & 3) * (2 * SLOT >> 4), xs = xlo + (((d >> 1) * XCH + (d & 1) * 64) >> 4);
        nb_sync(3, 256);
        WG_FENCE();
#pragma unroll
        for (int k = 0; k < 2; k++) {
          wgmma_ss_n96<1, 0>(a0, desc_mk(alo + ((4 * 4096 + k * 2048) >> 4)), desc_mk(xs + k * 2), (d | k) != 0);
          wgmma_ss_n96<1, 0>(a1, desc_mk(alo + ((5 * 4096 + k * 2048) >> 4)), desc_mk(xs + k * 2), (d | k) != 0);
          wgmma_ss_n32<1, 0>(b0, desc_mk(alo + ((6 * 4096 + k * 2048) >> 4)), desc_mk(xs + k * 2 + (64 * 128 >> 4)), (d | k) != 0);
          wgmma_ss_n32<1, 0>(b1, desc_mk(alo + ((7 * 4096 + k * 2048) >> 4)), desc_mk(xs + k * 2 + (64 * 128 >> 4)), (d | k) != 0);
        }
        WG_COMMIT();
        duties(d);
        WG_WAIT(0); fop(a0); fop(a1); fop(b0); fop(b1);
      }
    }
    TRACE(55);
    __syncthreads();
    TRACE(56);
    if (warp == 9 && elect()) issue_kv(4, 4);
    __syncwarp();
    {
      const int lane = tid_now() & 31;
      const int g = 2 * wiw + ((lane >> 3) & 1);
      const uint32_t base = sb + ((lane >> 4) * 8 + (lane & 7)) * 128 + ((g ^ (lane & 7)) << 4);
      const uint32_t t0 = base + (wg & 1) * 2 * QCH + (wg >> 1) * XCH;
#pragma unroll
      for (int j = 0; j < 12; j += 2) {
        stsm4t(t0 + j * 1024, pack(a0[4 * j], a0[4 * j + 1]), pack(a0[4 * j + 2], a0[4 * j + 3]), pack(a0[4 * j + 4], a0[4 * j + 5]), pack(a0[4 * j + 6], a0[4 * j + 7]));
        stsm4t(t0 + QCH + j * 1024, pack(a1[4 * j], a1[4 * j + 1]), pack(a1[4 * j + 2], a1[4 * j + 3]), pack(a1[4 * j + 4], a1[4 * j + 5]), pack(a1[4 * j + 6], a1[4 * j + 7]));
      }
      if (wg < 2) {
#pragma unroll
        for (int j = 0; j < 8; j += 2)
          stsm4t(base + (2 + wg) * QCH + XCH + j * 1024, pack(a2[4 * j], a2[4 * j + 1]), pack(a2[4 * j + 2], a2[4 * j + 3]), pack(a2[4 * j + 4], a2[4 * j + 5]), pack(a2[4 * j + 6], a2[4 * j + 7]));
      } else {
#pragma unroll
        for (int j = 0; j < 4; j += 2) {
          stsm4t(base + 2 * QCH + XCH + (8 + j) * 1024, pack(b0[4 * j], b0[4 * j + 1]), pack(b0[4 * j + 2], b0[4 * j + 3]), pack(b0[4 * j + 4], b0[4 * j + 5]), pack(b0[4 * j + 6], b0[4 * j + 7]));
          stsm4t(base + 3 * QCH + XCH + (8 + j) * 1024, pack(b1[4 * j], b1[4 * j + 1]), pack(b1[4 * j + 2], b1[4 * j + 3]), pack(b1[4 * j + 4], b1[4 * j + 5]), pack(b1[4 * j + 6], b1[4 * j + 7]));
        }
      }
    }
    proxy_fence();
    if (warp == 1) mbar_wait(kvfull, 0);
    __syncthreads();
  }
  TRACE(2); TRACEC(2, threadIdx.x == 0);

  {
    const uint32_t qlo = desc_lo(sb + wg * 8192, 16);
    float o[N1 / 2], park[N2 / 2];
    float m0, m1, l0 = 0.f, l1 = 0.f;
    const float c = 0.0625f * 1.4426950408889634f;
    int ks = 0;
    auto release = [&](int i, int slot) {
      if (elect()) {
        if (i + 5 < 2 * NT) {
          uint32_t e, g;
          asm volatile("ld.shared.u32 %0, [%1];" : "=r"(e) : "r"(tagp));
          asm volatile("ld.volatile.shared.u32 %0, [%1];" : "=r"(g) : "r"(sb + OFF_BAR + 1280) : "memory");
          const uint32_t need = e * (128u * 39u) + i * 128u - (kvh == 7 ? THR_7 : 0);
          if (i >= THR_I && (int)(g + THR_D + THR_S - need) < 0) {
            int n = 0;
            do { asm volatile("ld.relaxed.gpu.global.u32 %0, [%1];" : "=r"(g) : "l"(g_prog) : "memory"); } while ((int)(g + THR_D - need) < 0 && ++n < 64);
          }
        }
        if (i + 5 < 2 * NT) issue_kv(i + 5, slot);
        else if (i == 39) { issue_wo(0); issue_wo(1); }
        else if (i == 40) issue_wo(2);
        else if (i == 41) { issue_wo(3); issue_wo(4); }
        else issue_wo(5);
      }
      __syncwarp();
    };
    auto report = [&](int i) {
      if (i + 5 < 2 * NT && elect()) {
        asm volatile("red.relaxed.gpu.global.add.u32 [%0], 1;" ::"l"(g_prog) : "memory");
        asm volatile("cp.async.cg.shared.global [%0], [%1], 16;" ::"r"(sb + OFF_BAR + 1280), "l"(g_prog) : "memory");
      }
      __syncwarp();
    };
    auto step = [&](auto nc, int it) {
      constexpr int N = decltype(nc)::value;
      constexpr bool FIRST = (N == 16);
      float s[N / 2];
      const int vs = ks == 4 ? 0 : ks + 1;
      const uint32_t klo = desc_lo(sb + OFF_RING, 16) + ks * (KVS >> 4);
      if (!(FIRST && wg == 0)) nb_sync(1 + wg, 256);
      WG_FENCE();
#pragma unroll
      for (int kk = 0; kk < 16; kk++) {
        const uint64_t da = desc_mk(qlo + (((kk >> 2) * QCH + (kk & 3) * 32) >> 4)), db = desc_mk(klo + (((kk >> 2) * N * 128 + (kk & 3) * 32) >> 4));
        if constexpr (FIRST) wgmma_ss_n16<0, 0>(s, da, db, kk > 0); else wgmma_ss_n48<0, 0>(s, da, db, kk > 0);
      }
      WG_COMMIT();
      if (FIRST && wg == 0) nb_arrive(2, 256); else nb_arrive(wg == 0 ? 6 : (it == NT - 1 ? wg + 2 : wg + 3), 256);
      if (!FIRST && warp == 9) release(2 * it - 1, ks == 0 ? 4 : ks - 1);
      if (!FIRST && warp == THR_W) report(2 * it - 1);
      WG_WAIT(0); fop(s);
      float n0 = fmaxf(s[0], s[1]), n1 = fmaxf(s[2], s[3]);
#pragma unroll
      for (int i = 4; i < N / 2; i += 4) { n0 = fmaxf(n0, fmaxf(s[i], s[i + 1])); n1 = fmaxf(n1, fmaxf(s[i + 2], s[i + 3])); }
      n0 *= c; n1 *= c;
      if (FIRST || __any_sync(0xffffffffu, fmaxf(n0 - m0, n1 - m1) > 8.f)) {
        if (!FIRST) { n0 = fmaxf(n0, m0); n1 = fmaxf(n1, m1); }
        n0 = fmaxf(n0, __shfl_xor_sync(0xffffffffu, n0, 1)); n1 = fmaxf(n1, __shfl_xor_sync(0xffffffffu, n1, 1));
        n0 = fmaxf(n0, __shfl_xor_sync(0xffffffffu, n0, 2)); n1 = fmaxf(n1, __shfl_xor_sync(0xffffffffu, n1, 2));
        if (!FIRST) {
          const float a0 = ex2(m0 - n0), a1 = ex2(m1 - n1);
          l0 *= a0; l1 *= a1;
#pragma unroll
          for (int i = 0; i < N1 / 2; i += 4) { o[i] *= a0; o[i + 1] *= a0; o[i + 2] *= a1; o[i + 3] *= a1; }
#pragma unroll
          for (int i = 0; i < N2 / 2; i += 4) { park[i] *= a0; park[i + 1] *= a0; park[i + 2] *= a1; park[i + 3] *= a1; }
        }
        m0 = n0; m1 = n1;
      }
      uint32_t p[N / 4];
#pragma unroll
      for (int i = N / 2 - 4; i >= 0; i -= 4) {
        const float e0 = ex2(fmaf(s[i], c, -m0)), e1 = ex2(fmaf(s[i + 1], c, -m0)), e2 = ex2(fmaf(s[i + 2], c, -m1)), e3 = ex2(fmaf(s[i + 3], c, -m1));
        l0 += e0 + e1; l1 += e2 + e3;
        p[i / 2] = pack(e0, e1); p[i / 2 + 1] = pack(e2, e3);
      }
      if (!FIRST) fop(o);
      const uint32_t vlo = desc_lo(sb + OFF_RING, N * 128) + vs * (KVS >> 4);
      const uint32_t dep = (__float_as_uint(l0) | __float_as_uint(l1)) & zero;
      if (warp == 1) mbar_wait(kvfull + 8 * (2 * it + 1) + dep, 0);
      nb_sync(4 + wg + dep, 256);
      float o2[N2 / 2];
      WG_FENCE();
#pragma unroll
      for (int kk = 0; kk < N / 16; kk++) {
        const uint64_t db = desc_mk(vlo + ((kk * 2048) >> 4)), db2 = desc_mk(vlo + ((kk * 2048 + 3 * N * 128 + (N1 - 192) * 2) >> 4));
        wgmma_rs_n232<1>(o, p[kk * 4], p[kk * 4 + 1], p[kk * 4 + 2], p[kk * 4 + 3], db, !FIRST);
        wgmma_rs_n24<1>(o2, p[kk * 4], p[kk * 4 + 1], p[kk * 4 + 2], p[kk * 4 + 3], db2, kk);
      }
      WG_COMMIT();
      if (it < NT - 1) nb_arrive(1 + (wg == 0 ? 2 : wg - 1), 256);
      else if (wg < 2) nb_arrive(5 + wg, 256);
      if (warp == 9) release(2 * it, ks);
      if (warp == THR_W) report(2 * it);
      if (warp == 1 && it + 1 < NT) mbar_wait(kvfull + 8 * (2 * it + 2), 0);
      ks = vs == 4 ? 0 : vs + 1;
      if ((it & 3) == 0) { TRACEW(57 + (it >> 2), threadIdx.x == 192); TRACEC(57 + (it >> 2), threadIdx.x == 192); }
      WG_WAIT(0); fop(o); fop(o2);
#pragma unroll
      for (int i = 0; i < N2 / 2; i++) { if (FIRST) asm volatile("mov.b32 %0, %1;" : "=f"(park[i]) : "f"(o2[i])); else park[i] += o2[i]; }
    };
    step(IC<16>(), 0);
#pragma unroll 1
    for (int it = 1; it < NT; it++) step(IC<48>(), it);
    TRACE(3); TRACEW(6, threadIdx.x == 256);
    if (wg < 2) nb_arrive(1, 384);
    else { nb_sync(1, 384); if (warp == 8 && elect()) { issue_wo(6); issue_wo(7); } __syncwarp(); }
    l0 += __shfl_xor_sync(0xffffffffu, l0, 1); l1 += __shfl_xor_sync(0xffffffffu, l1, 1);
    l0 += __shfl_xor_sync(0xffffffffu, l0, 2); l1 += __shfl_xor_sync(0xffffffffu, l1, 2);
    const float r0 = rcp(l0), r1 = rcp(l1);
    const int lane = tid_now() & 31;
    const uint32_t base = sb + (wg * 64 + wiw * 16 + (lane & 7) + ((lane >> 3) & 1) * 8) * 128;
#pragma unroll
    for (int j = 0; j < 32; j += 2) {
      float v[8];
#pragma unroll
      for (int i = 0; i < 8; i++) { const int q = 4 * j + i; v[i] = (q < N1 / 2 ? o[q < N1 / 2 ? q : 0] : park[q >= N1 / 2 ? q - N1 / 2 : 0]);
        v[i] *= (i & 2) ? r1 : r0;
      }
      const int g = j + (lane >> 4);
      stsm4(base + (j >> 3) * QCH + (((g & 7) ^ (lane & 7)) << 4), pack(v[0], v[1]), pack(v[2], v[3]), pack(v[4], v[5]), pack(v[6], v[7]));
    }
    proxy_fence();
    if (wg == 0) nb_sync(2, 256); else nb_arrive(1 + wg, 256);
  }
  TRACE(4); TRACEW(13, threadIdx.x == 256);

  {
    const int tw = tid_now() & 127, lane = tw & 31;
    uint32_t epoch;
    asm volatile("ld.shared.u32 %0, [%1];" : "=r"(epoch) : "r"(tagp));
    uint32_t tag = (epoch + 1) & 1;
    asm volatile("" : "+r"(tag));
    const uint32_t hand = sb + OFF_RING + 2 * SLOT;
    if (wg == 0) {
      uint32_t al = desc_lo(sb + OFF_RING, 2048), ol = desc_lo(sb, 16);
      float accA[48], accB[48];
      uint4* gsend = g_part + ((grp * 7 + (kvh == 7 ? 0 : kvh + 1)) * 8 + kvh) * 768 + tw;
      const int wrap = kvh == 7 ? 7 : 6 - kvh;
      auto send = [&](float (&acc)[48], int p, int i0, int i1) {
        uint4* pp = gsend + (p >= wrap ? p - 7 : p) * (8 * 768);
#pragma unroll
        for (int i = i0; i < i1; i++) {
          const uint32_t x = set_tag(pack(acc[8 * i], acc[8 * i + 1]), tag), y = pack(acc[8 * i + 2], acc[8 * i + 3]);
          const uint32_t z = set_tag(pack(acc[8 * i + 4], acc[8 * i + 5]), tag), w = pack(acc[8 * i + 6], acc[8 * i + 7]);
          asm volatile("st.relaxed.gpu.global.v2.b64 [%0], {%1,%2};" ::"l"(pp + i * 128), "l"((uint64_t)x | ((uint64_t)y << 32)), "l"((uint64_t)z | ((uint64_t)w << 32)) : "memory");
        }
      };
      auto chunk = [&](float (&acc)[48], int L, int q) {
        if ((L & 1) == 0) nb_sync(RDY_ID((L >> 1) & 3), 160);
        asm volatile("add.u32 %0, %0, %1;" : "+r"(al) : "r"(zero)); asm volatile("add.u32 %0, %0, %1;" : "+r"(ol) : "r"(zero));
        WG_FENCE();
#pragma unroll
        for (int ks = 0; ks < 8; ks++)
          wgmma_ss_n96<1, 0>(acc, desc_mk(al + ((L + 6) & 7) * (SLOT >> 4) + ks * (2048 >> 4)),
                             desc_mk(ol + (((2 * (q & 1) + (ks >> 2)) * QCH + (q >> 1) * XCH + (ks & 3) * 32) >> 4)), (q | ks) != 0);
        WG_COMMIT();
        WG_WAIT(1);
        if (L > 0 && L <= 20) nb_arrive(7 + ((L - 1) & 7), 160);
      };
      auto tile = [&](float (&acc)[48], float (&prev)[48], int p) {
#pragma unroll
        for (int q = 0; q < 4; q++) {
          chunk(acc, 4 * p + q, q);
          if (q == 0) { fop(prev); TRACEW(24 + p - 1, tw == 0); TRACEC(24 + p - 1, tw == 0); }
          if (q < SENDQ) send(prev, p - 1, q * (6 / SENDQ), (q + 1) * (6 / SENDQ));
          if (q == SENDQ - 1) TRACEW(32 + p - 1, tw == 0);
        }
      };
      chunk(accA, 0, 0); chunk(accA, 1, 1); chunk(accB, 2, 0); chunk(accB, 3, 1);
      nb_sync(3, 256);
      chunk(accA, 4, 2); chunk(accA, 5, 3);
      chunk(accB, 6, 2); fop(accA); TRACEW(24, tw == 0); send(accA, 0, 0, 3);
      chunk(accB, 7, 3); send(accA, 0, 3, 6); TRACEW(32, tw == 0);
      tile(accA, accB, 2); tile(accB, accA, 3); tile(accA, accB, 4); tile(accB, accA, 5); tile(accA, accB, 6);
      WG_WAIT(0); fop(accA);
      TRACEW(30, tw == 0); TRACEC(30, tw == 0);
      if (kvh == 7) { send(accA, 6, 0, 6); TRACEW(38, tw == 0); }
      else {
#pragma unroll
        for (int i = 0; i < 12; i++)
          asm volatile("st.shared.v4.f32 [%0], {%1,%2,%3,%4};" ::"r"(hand + (i * 128 + tw) * 16),
                       "f"(accA[4 * i]), "f"(accA[4 * i + 1]), "f"(accA[4 * i + 2]), "f"(accA[4 * i + 3]) : "memory");
        __syncwarp();
        if (elect()) mbar_arrive(accrdy);
      }
    } else if (warp == 7) {
      for (int h = 0; h < 14; h++) {
        mbar_wait(wofull + 16 * h, 0);
        mbar_wait(wofull + 16 * h + 8, 0);
        nb_arrive(RDY_ID(h & 3), 160);
      }
    } else if (warp == 6) {
      for (int L = 0; L + 8 < NWO; L++) {
        nb_sync(7 + (L & 7), 160);
        if (elect()) issue_wo(L + 8);
        __syncwarp();
      }
    } else if (kvh != 7) {
      const int f = warp >= 8 ? warp - 8 : warp;
      auto src_of = [&](int k) {
        const int k7 = kvh > 0 ? kvh - 1 : 0;
        int sidx = kvh - 1 - (k > k7 ? k - 1 : k); if (sidx < 0) sidx += 7;
        return k == k7 ? 7 : sidx;
      };
      const uint4* gown = g_part + (grp * 7 + kvh) * 8 * 768 + f * 128;
      const uint4* pprobe = gown + src_of(lane < 7 ? lane : 0) * 768 + 127;
      const uint32_t hu = hand + f * 4096;
      const uint32_t ident = (lane >> 3) == (lane & 3) ? (0x3f80u << (((lane >> 2) & 1) * 16)) : 0u;
      uint4 v[7][4];
      auto fetch = [&](uint4 (&d)[4], int k) {
        const uint4* pp = gown + src_of(k) * 768 + lane;
#pragma unroll
        for (int i = 0; i < 4; i++) {
          uint64_t a, b;
          asm volatile("ld.relaxed.gpu.global.v2.b64 {%0,%1}, [%2];" : "=l"(a), "=l"(b) : "l"(pp + i * 32) : "memory");
          d[i] = make_uint4((uint32_t)a, (uint32_t)(a >> 32), (uint32_t)b, (uint32_t)(b >> 32));
        }
      };
      int spins = 0;
      auto recheck = [&](uint4 (&d)[4], int k) {
        for (;;) {
          uint32_t bad = 0;
#pragma unroll
          for (int i = 0; i < 4; i++) bad |= (d[i].x ^ tag) | (d[i].z ^ tag);
          if (!__any_sync(0xffffffffu, bad & 1)) break;
          fetch(d, k);
          if (++spins > 8000000) __trap();
        }
      };
      {
        constexpr int pass = 1;
        if (pass) {
          uint32_t seen = 0;
#pragma unroll
          for (int k = 0; k < 7; k++) {
            while (!((seen >> k) & 1)) {
              uint32_t pr;
              asm volatile("ld.relaxed.gpu.global.u32 %0, [%1];" : "=r"(pr) : "l"(pprobe) : "memory");
              seen = __ballot_sync(0xffffffffu, ((pr ^ tag) & 1) == 0);
              if (++spins > 8000000) __trap();
            }
            fetch(v[k], k);
            TRACEW(16 + k, threadIdx.x == 288);
          }
        }
        float sum[32];
#pragma unroll
        for (int i = 0; i < 32; i++) sum[i] = 0.f;
        {
          uint32_t bad = 0;
#pragma unroll
          for (int k = 0; k < 6; k++)
#pragma unroll
            for (int i = 0; i < 4; i++) bad |= (v[k][i].x ^ tag) | (v[k][i].z ^ tag);
          if (__any_sync(0xffffffffu, bad & 1)) {
#pragma unroll
            for (int k = 0; k < 6; k++) recheck(v[k], k);
          }
        }
#pragma unroll
        for (int k = 0; k < 7; k++) {
          if (k == 6) {
            if (pass) mbar_wait(accrdy, 0);
#pragma unroll
            for (int i = 0; i < 8; i++) {
              float4 x;
              asm volatile("ld.shared.v4.f32 {%0,%1,%2,%3}, [%4];" : "=f"(x.x), "=f"(x.y), "=f"(x.z), "=f"(x.w) : "r"(hu + (i & 1) * 2048 + (i >> 1) * 512 + lane * 16) : "memory");
              sum[4 * i] += x.x; sum[4 * i + 1] += x.y; sum[4 * i + 2] += x.z; sum[4 * i + 3] += x.w;
            }
            TRACEW(44, threadIdx.x == 288);
            recheck(v[6], 6);
          }
#pragma unroll
          for (int i = 0; i < 4; i++) {
            mma_add(sum[8 * i], sum[8 * i + 1], sum[8 * i + 2], sum[8 * i + 3], v[k][i].x, v[k][i].y, ident, pass);
            mma_add(sum[8 * i + 4], sum[8 * i + 5], sum[8 * i + 6], sum[8 * i + 7], v[k][i].z, v[k][i].w, ident, pass);
          }
        }
        TRACEW(40, threadIdx.x == 288); TRACEW(41, threadIdx.x == 160);
        __syncwarp();
        const int r = (lane >> 4) * 8 + (lane & 7), h = (lane >> 3) & 1;
        const uint32_t sa = pass ? hu + r * 128 : sb + OFF_BAR + 1024;
#pragma unroll
        for (int k = 0; k < 4; k++)
          stsm4t(sa + (((2 * k + h) ^ (r & 7)) << 4), pack(sum[8 * k], sum[8 * k + 1]), pack(sum[8 * k + 2], sum[8 * k + 3]),
                 pack(sum[8 * k + 4], sum[8 * k + 5]), pack(sum[8 * k + 6], sum[8 * k + 7]));
        __syncwarp();
        __nv_bfloat16* ob = out + (size_t)(bb * SQ + f * 16 + (lane >> 3)) * (2 * DM) + blk * DM + kvh * 64 + (lane & 7) * 8;
#pragma unroll
        for (int k = 0; k < 4; k++) {
          const int row = k * 4 + (lane >> 3);
          uint4 x;
          asm volatile("ld.shared.v4.u32 {%0,%1,%2,%3}, [%4];" : "=r"(x.x), "=r"(x.y), "=r"(x.z), "=r"(x.w) : "r"(hu + row * 128 + (((lane & 7) ^ (row & 7)) << 4)) : "memory");
          if (pass) *reinterpret_cast<uint4*>(ob + (size_t)(k * 4) * (2 * DM)) = x;
        }
      }
      if (kvh == 0 && warp == 9 && lane == 0) g_epoch[grp * 32] = epoch + 1;
    }
  }
  TRACEW(5, threadIdx.x == (kvh == 7 ? 0 : 288)); TRACEW(7, threadIdx.x == 160);
}

typedef CUresult (*EncodeFn)(CUtensorMap*, CUtensorMapDataType, cuuint32_t, void*, const cuuint64_t*, const cuuint64_t*, const cuuint32_t*,
                             const cuuint32_t*, CUtensorMapInterleave, CUtensorMapSwizzle, CUtensorMapL2promotion, CUtensorMapFloatOOBfill);

void make_map(EncodeFn fn, CUtensorMap* m, void* ptr, uint64_t rows, uint64_t cols, uint32_t brows, uint32_t bchunks) {
  cuuint64_t dims[3] = {64, rows, cols / 64};
  cuuint64_t strides[2] = {cols * 2, 128};
  cuuint32_t box[3] = {64, brows, bchunks};
  cuuint32_t es[3] = {1, 1, 1};
  fn(m, CU_TENSOR_MAP_DATA_TYPE_BFLOAT16, 3, ptr, dims, strides, box, es, CU_TENSOR_MAP_INTERLEAVE_NONE, CU_TENSOR_MAP_SWIZZLE_128B,
     CU_TENSOR_MAP_L2_PROMOTION_L2_256B, CU_TENSOR_MAP_FLOAT_OOB_FILL_NONE);
}

}

extern "C" void kernel_launch(void* const* d_in, const int* in_sizes, int n_in, void* d_out, int out_size) {
  static EncodeFn fn = nullptr;
  if (!fn) {
    void* p = nullptr; cudaDriverEntryPointQueryResult qr;
    cudaGetDriverEntryPoint("cuTensorMapEncodeTiled", &p, cudaEnableDefault, &qr);
    fn = (EncodeFn)p;
    cudaFuncSetAttribute(gqa_fused_kernel, cudaFuncAttributeMaxDynamicSharedMemorySize, SMEM_BYTES);
  }
  Params prm;
  for (int b = 0; b < 2; b++) {
    make_map(fn, &prm.m[b * 7 + 0], d_in[b * 5 + 0], 768, 448, 96, 1);
    make_map(fn, &prm.m[b * 7 + 1], d_in[b * 5 + 1], 65536, 256, 48, 4);
    make_map(fn, &prm.m[b * 7 + 2], d_in[b * 5 + 2], 65536, 256, 48, 4);
    make_map(fn, &prm.m[b * 7 + 3], d_in[b * 5 + 3], 448, 4096, 32, 8);
    make_map(fn, &prm.m[b * 7 + 4], d_in[b * 5 + 4], 4096, 448, 128, 1);
    make_map(fn, &prm.m[b * 7 + 5], d_in[b * 5 + 1], 65536, 256, 16, 4);
    make_map(fn, &prm.m[b * 7 + 6], d_in[b * 5 + 2], 65536, 256, 16, 4);
  }
  prm.kv[0] = (const char*)d_in[1]; prm.kv[1] = (const char*)d_in[2]; prm.kv[2] = (const char*)d_in[6]; prm.kv[3] = (const char*)d_in[7]; prm.kv[4] = (const char*)d_in[3]; prm.kv[5] = (const char*)d_in[8]; prm.kv[6] = (const char*)d_in[4]; prm.kv[7] = (const char*)d_in[9];
  gqa_fused_kernel<<<128, 384, SMEM_BYTES, cudaStreamPerThread>>>(prm, (__nv_bfloat16*)d_out, 0u);
}
```

```cpp
#include <cuda_runtime.h>
#include <cuda_bf16.h>
#include <cuda.h>
#include <stdint.h>

namespace {

constexpr int SQ = 96, DM = 448, SK = 1024;
constexpr int SLOT = 16384;
constexpr int KVS = 24576;
constexpr int OFF_RING = 98304;
constexpr int OFF_BAR = OFF_RING + 8 * SLOT;
constexpr int SMEM_BYTES = OFF_BAR + 1792;
constexpr int QCH = 24576;
constexpr int XCH = 12288;
constexpr int NT = 22;
constexpr int NWO = 28;
constexpr int N1 = 232, N2 = 24;
constexpr int PF_U = 16, PF_J0 = 4;
constexpr int THR_K = 132, THR_D = 130;
constexpr int THR_S = 64;
constexpr int THR_7 = 128;

struct Params {
  CUtensorMap m[14];
  const char* v[2];
  const char* wq[2];
};

__device__ uint4 g_part[16 * 7 * 8 * 768];
__device__ uint4 g_prog[16];
__device__ uint32_t g_epoch[16 * 32];

template<int TA, int TB> __device__ __forceinline__ void wgmma_ss_n16(float (&d)[8], uint64_t da, uint64_t db, int sd) {
  asm volatile("{\n.reg .pred p;\nsetp.ne.b32 p, %10, 0;\n"
   "wgmma.mma_async.sync.aligned.m64n16k16.f32.bf16.bf16 {"
   "%0, %1, %2, %3, %4, %5, %6, %7"
   "}, %8, %9, p, 1, 1, %11, %12;\n}\n"
   : "+f"(d[0]), "+f"(d[1]), "+f"(d[2]), "+f"(d[3]), "+f"(d[4]), "+f"(d[5]), "+f"(d[6]), "+f"(d[7])
   : "l"(da), "l"(db), "r"(sd), "n"(TA), "n"(TB));
}
template<int TA, int TB> __device__ __forceinline__ void wgmma_ss_n32(float (&d)[16], uint64_t da, uint64_t db, int sd) {
  asm volatile("{\n.reg .pred p;\nsetp.ne.b32 p, %18, 0;\n"
   "wgmma.mma_async.sync.aligned.m64n32k16.f32.bf16.bf16 {"
   "%0, %1, %2, %3, %4, %5, %6, %7, %8, %9, %10, %11, %12, %13, %14, %15"
   "}, %16, %17, p, 1, 1, %19, %20;\n}\n"
   : "+f"(d[0]), "+f"(d[1]), "+f"(d[2]), "+f"(d[3]), "+f"(d[4]), "+f"(d[5]), "+f"(d[6]), "+f"(d[7]),
     "+f"(d[8]), "+f"(d[9]), "+f"(d[10]), "+f"(d[11]), "+f"(d[12]), "+f"(d[13]), "+f"(d[14]), "+f"(d[15])
   : "l"(da), "l"(db), "r"(sd), "n"(TA), "n"(TB));
}
template<int TA, int TB> __device__ __forceinline__ void wgmma_ss_n48(float (&d)[24], uint64_t da, uint64_t db, int sd) {
  asm volatile("{\n.reg .pred p;\nsetp.ne.b32 p, %26, 0;\n"
   "wgmma.mma_async.sync.aligned.m64n48k16.f32.bf16.bf16 {"
   "%0, %1, %2, %3, %4, %5, %6, %7, %8, %9, %10, %11, %12, %13, %14, %15, "
   "%16, %17, %18, %19, %20, %21, %22, %23"
   "}, %24, %25, p, 1, 1, %27, %28;\n}\n"
   : "+f"(d[0]), "+f"(d[1]), "+f"(d[2]), "+f"(d[3]), "+f"(d[4]), "+f"(d[5]), "+f"(d[6]), "+f"(d[7]),
     "+f"(d[8]), "+f"(d[9]), "+f"(d[10]), "+f"(d[11]), "+f"(d[12]), "+f"(d[13]), "+f"(d[14]), "+f"(d[15]),
     "+f"(d[16]), "+f"(d[17]), "+f"(d[18]), "+f"(d[19]), "+f"(d[20]), "+f"(d[21]), "+f"(d[22]), "+f"(d[23])
   : "l"(da), "l"(db), "r"(sd), "n"(TA), "n"(TB));
}
template<int TA, int TB> __device__ __forceinline__ void wgmma_ss_n64(float (&d)[32], uint64_t da, uint64_t db, int sd) {
  asm volatile("{\n.reg .pred p;\nsetp.ne.b32 p, %34, 0;\n"
   "wgmma.mma_async.sync.aligned.m64n64k16.f32.bf16.bf16 {"
   "%0, %1, %2, %3, %4, %5, %6, %7, %8, %9, %10, %11, %12, %13, %14, %15, "
   "%16, %17, %18, %19, %20, %21, %22, %23, %24, %25, %26, %27, %28, %29, %30, %31"
   "}, %32, %33, p, 1, 1, %35, %36;\n}\n"
   : "+f"(d[0]), "+f"(d[1]), "+f"(d[2]), "+f"(d[3]), "+f"(d[4]), "+f"(d[5]), "+f"(d[6]), "+f"(d[7]),
     "+f"(d[8]), "+f"(d[9]), "+f"(d[10]), "+f"(d[11]), "+f"(d[12]), "+f"(d[13]), "+f"(d[14]), "+f"(d[15]),
     "+f"(d[16]), "+f"(d[17]), "+f"(d[18]), "+f"(d[19]), "+f"(d[20]), "+f"(d[21]), "+f"(d[22]), "+f"(d[23]),
     "+f"(d[24]), "+f"(d[25]), "+f"(d[26]), "+f"(d[27]), "+f"(d[28]), "+f"(d[29]), "+f"(d[30]), "+f"(d[31])
   : "l"(da), "l"(db), "r"(sd), "n"(TA), "n"(TB));
}
template<int TA, int TB> __device__ __forceinline__ void wgmma_ss_n96(float (&d)[48], uint64_t da, uint64_t db, int sd) {
  asm volatile("{\n.reg .pred p;\nsetp.ne.b32 p, %50, 0;\n"
   "wgmma.mma_async.sync.aligned.m64n96k16.f32.bf16.bf16 {"
   "%0, %1, %2, %3, %4, %5, %6, %7, %8, %9, %10, %11, %12, %13, %14, %15, "
   "%16, %17, %18, %19, %20, %21, %22, %23, %24, %25, %26, %27, %28, %29, %30, %31, "
   "%32, %33, %34, %35, %36, %37, %38, %39, %40, %41, %42, %43, %44, %45, %46, %47"
   "}, %48, %49, p, 1, 1, %51, %52;\n}\n"
   : "+f"(d[0]), "+f"(d[1]), "+f"(d[2]), "+f"(d[3]), "+f"(d[4]), "+f"(d[5]), "+f"(d[6]), "+f"(d[7]),
     "+f"(d[8]), "+f"(d[9]), "+f"(d[10]), "+f"(d[11]), "+f"(d[12]), "+f"(d[13]), "+f"(d[14]), "+f"(d[15]),
     "+f"(d[16]), "+f"(d[17]), "+f"(d[18]), "+f"(d[19]), "+f"(d[20]), "+f"(d[21]), "+f"(d[22]), "+f"(d[23]),
     "+f"(d[24]), "+f"(d[25]), "+f"(d[26]), "+f"(d[27]), "+f"(d[28]), "+f"(d[29]), "+f"(d[30]), "+f"(d[31]),
     "+f"(d[32]), "+f"(d[33]), "+f"(d[34]), "+f"(d[35]), "+f"(d[36]), "+f"(d[37]), "+f"(d[38]), "+f"(d[39]),
     "+f"(d[40]), "+f"(d[41]), "+f"(d[42]), "+f"(d[43]), "+f"(d[44]), "+f"(d[45]), "+f"(d[46]), "+f"(d[47])
   : "l"(da), "l"(db), "r"(sd), "n"(TA), "n"(TB));
}
template<int TB> __device__ __forceinline__ void wgmma_rs_n24(float (&d)[12], uint32_t a0, uint32_t a1, uint32_t a2, uint32_t a3, uint64_t db, int sd) {
  asm volatile("{\n.reg .pred p;\nsetp.ne.b32 p, %17, 0;\n"
   "wgmma.mma_async.sync.aligned.m64n24k16.f32.bf16.bf16 {"
   "%0, %1, %2, %3, %4, %5, %6, %7, %8, %9, %10, %11"
   "}, {%12, %13, %14, %15}, %16, p, 1, 1, %18;\n}\n"
   : "+f"(d[0]), "+f"(d[1]), "+f"(d[2]), "+f"(d[3]), "+f"(d[4]), "+f"(d[5]), "+f"(d[6]), "+f"(d[7]),
     "+f"(d[8]), "+f"(d[9]), "+f"(d[10]), "+f"(d[11])
   : "r"(a0), "r"(a1), "r"(a2), "r"(a3), "l"(db), "r"(sd), "n"(TB));
}
template<int TB> __device__ __forceinline__ void wgmma_rs_n232(float (&d)[116], uint32_t a0, uint32_t a1, uint32_t a2, uint32_t a3, uint64_t db, int sd) {
  asm volatile("{\n.reg .pred p;\nsetp.ne.b32 p, %121, 0;\n"
   "wgmma.mma_async.sync.aligned.m64n232k16.f32.bf16.bf16 {"
   "%0, %1, %2, %3, %4, %5, %6, %7, %8, %9, %10, %11, %12, %13, %14, %15, "
   "%16, %17, %18, %19, %20, %21, %22, %23, %24, %25, %26, %27, %28, %29, %30, %31, "
   "%32, %33, %34, %35, %36, %37, %38, %39, %40, %41, %42, %43, %44, %45, %46, %47, "
   "%48, %49, %50, %51, %52, %53, %54, %55, %56, %57, %58, %59, %60, %61, %62, %63, "
   "%64, %65, %66, %67, %68, %69, %70, %71, %72, %73, %74, %75, %76, %77, %78, %79, "
   "%80, %81, %82, %83, %84, %85, %86, %87, %88, %89, %90, %91, %92, %93, %94, %95, "
   "%96, %97, %98, %99, %100, %101, %102, %103, %104, %105, %106, %107, %108, %109, %110, %111, "
   "%112, %113, %114, %115"
   "}, {%116, %117, %118, %119}, %120, p, 1, 1, %122;\n}\n"
   : "+f"(d[0]), "+f"(d[1]), "+f"(d[2]), "+f"(d[3]), "+f"(d[4]), "+f"(d[5]), "+f"(d[6]), "+f"(d[7]),
     "+f"(d[8]), "+f"(d[9]), "+f"(d[10]), "+f"(d[11]), "+f"(d[12]), "+f"(d[13]), "+f"(d[14]), "+f"(d[15]),
     "+f"(d[16]), "+f"(d[17]), "+f"(d[18]), "+f"(d[19]), "+f"(d[20]), "+f"(d[21]), "+f"(d[22]), "+f"(d[23]),
     "+f"(d[24]), "+f"(d[25]), "+f"(d[26]), "+f"(d[27]), "+f"(d[28]), "+f"(d[29]), "+f"(d[30]), "+f"(d[31]),
     "+f"(d[32]), "+f"(d[33]), "+f"(d[34]), "+f"(d[35]), "+f"(d[36]), "+f"(d[37]), "+f"(d[38]), "+f"(d[39]),
     "+f"(d[40]), "+f"(d[41]), "+f"(d[42]), "+f"(d[43]), "+f"(d[44]), "+f"(d[45]), "+f"(d[46]), "+f"(d[47]),
     "+f"(d[48]), "+f"(d[49]), "+f"(d[50]), "+f"(d[51]), "+f"(d[52]), "+f"(d[53]), "+f"(d[54]), "+f"(d[55]),
     "+f"(d[56]), "+f"(d[57]), "+f"(d[58]), "+f"(d[59]), "+f"(d[60]), "+f"(d[61]), "+f"(d[62]), "+f"(d[63]),
     "+f"(d[64]), "+f"(d[65]), "+f"(d[66]), "+f"(d[67]), "+f"(d[68]), "+f"(d[69]), "+f"(d[70]), "+f"(d[71]),
     "+f"(d[72]), "+f"(d[73]), "+f"(d[74]), "+f"(d[75]), "+f"(d[76]), "+f"(d[77]), "+f"(d[78]), "+f"(d[79]),
     "+f"(d[80]), "+f"(d[81]), "+f"(d[82]), "+f"(d[83]), "+f"(d[84]), "+f"(d[85]), "+f"(d[86]), "+f"(d[87]),
     "+f"(d[88]), "+f"(d[89]), "+f"(d[90]), "+f"(d[91]), "+f"(d[92]), "+f"(d[93]), "+f"(d[94]), "+f"(d[95]),
     "+f"(d[96]), "+f"(d[97]), "+f"(d[98]), "+f"(d[99]), "+f"(d[100]), "+f"(d[101]), "+f"(d[102]), "+f"(d[103]),
     "+f"(d[104]), "+f"(d[105]), "+f"(d[106]), "+f"(d[107]), "+f"(d[108]), "+f"(d[109]), "+f"(d[110]), "+f"(d[111]),
     "+f"(d[112]), "+f"(d[113]), "+f"(d[114]), "+f"(d[115])
   : "r"(a0), "r"(a1), "r"(a2), "r"(a3), "l"(db), "r"(sd), "n"(TB));
}


__device__ __forceinline__ void mbar_init(uint32_t a, uint32_t c) { asm volatile("mbarrier.init.shared::cta.b64 [%0], %1;" ::"r"(a), "r"(c) : "memory"); }
__device__ __forceinline__ void mbar_expect_tx(uint32_t a, uint32_t b) { asm volatile("mbarrier.arrive.expect_tx.shared::cta.b64 _, [%0], %1;" ::"r"(a), "r"(b) : "memory"); }
__device__ __forceinline__ void mbar_arrive(uint32_t a) { asm volatile("mbarrier.arrive.shared::cta.b64 _, [%0];" ::"r"(a) : "memory"); }
__device__ __forceinline__ void mbar_wait(uint32_t a, uint32_t p) {
  asm volatile("{\n.reg .pred P1;\n.reg .u32 c;\nmov.u32 c, 0;\nWAIT_LOOP:\n"
               "mbarrier.try_wait.parity.shared::cta.b64 P1, [%0], %1;\n@P1 bra DONE;\n"
               "add.u32 c, c, 1;\nsetp.lt.u32 P1, c, 4000000;\n@P1 bra WAIT_LOOP;\ntrap;\nDONE:\n}" ::"r"(a), "r"(p) : "memory");
}
__device__ __forceinline__ void tma3d(uint32_t dst, const CUtensorMap* map, int c1, int c2, uint32_t bar) {
  asm volatile("cp.async.bulk.tensor.3d.shared::cluster.global.mbarrier::complete_tx::bytes [%0], [%1, {%2, %3, %4}], [%5];"
               ::"r"(dst), "l"(map), "r"(0), "r"(c1), "r"(c2), "r"(bar) : "memory");
}
__device__ __forceinline__ uint32_t desc_lo(uint32_t addr, uint32_t lbo) { return ((addr & 0x3FFFF) >> 4) | ((lbo >> 4) << 16); }
__device__ __forceinline__ uint64_t desc_mk(uint32_t lo) { uint64_t d; asm("mov.b64 %0, {%1, %2};" : "=l"(d) : "r"(lo), "r"(0x40000040)); return d; }
#define WG_FENCE() asm volatile("wgmma.fence.sync.aligned;" ::: "memory")
#define WG_COMMIT() asm volatile("wgmma.commit_group.sync.aligned;" ::: "memory")
#define WG_WAIT(n) asm volatile("wgmma.wait_group.sync.aligned %0;" ::"n"(n) : "memory")
template <int N> __device__ __forceinline__ void fop(float (&d)[N]) {
#pragma unroll
  for (int i = 0; i < N; i++) asm volatile("" : "+f"(d[i])::"memory");
}
__device__ __forceinline__ uint32_t pack(float a, float b) { uint32_t r; asm("cvt.rn.bf16x2.f32 %0, %1, %2;" : "=r"(r) : "f"(b), "f"(a)); return r; }
__device__ __forceinline__ float ex2(float x) { float y; asm("ex2.approx.ftz.f32 %0, %1;" : "=f"(y) : "f"(x)); return y; }
__device__ __forceinline__ float rcp(float x) { float y; asm("rcp.approx.ftz.f32 %0, %1;" : "=f"(y) : "f"(x)); return y; }
__device__ __forceinline__ void nb_sync(int id, int n) { asm volatile("bar.sync %0, %1;" ::"r"(id), "r"(n) : "memory"); }
__device__ __forceinline__ void nb_arrive(int id, int n) { asm volatile("bar.arrive %0, %1;" ::"r"(id), "r"(n) : "memory"); }
__device__ __forceinline__ bool elect() { uint32_t p; asm volatile("{\n.reg .pred P;\nelect.sync _|P, 0xffffffff;\nselp.u32 %0,1,0,P;\n}" : "=r"(p)); return p; }
__device__ __forceinline__ void stsm4(uint32_t a, uint32_t r0, uint32_t r1, uint32_t r2, uint32_t r3) {
  asm volatile("stmatrix.sync.aligned.m8n8.x4.shared.b16 [%0], {%1,%2,%3,%4};" ::"r"(a), "r"(r0), "r"(r1), "r"(r2), "r"(r3) : "memory");
}
__device__ __forceinline__ void stsm4t(uint32_t a, uint32_t r0, uint32_t r1, uint32_t r2, uint32_t r3) {
  asm volatile("stmatrix.sync.aligned.m8n8.x4.trans.shared.b16 [%0], {%1,%2,%3,%4};" ::"r"(a), "r"(r0), "r"(r1), "r"(r2), "r"(r3) : "memory");
}
template <int N> __device__ __forceinline__ void stsm4t_acc(uint32_t a, const float (&d)[N], int i) {
  stsm4t(a, pack(d[i], d[i + 1]), pack(d[i + 2], d[i + 3]), pack(d[i + 4], d[i + 5]), pack(d[i + 6], d[i + 7]));
}
__device__ __forceinline__ void l2_pull(uint32_t dump, const void* g) { asm volatile("cp.async.ca.shared.global.L2::256B [%0], [%1], 4;" ::"r"(dump), "l"(g) : "memory"); }
__device__ __forceinline__ void mma_add(float& d0, float& d1, float& d2, float& d3, uint32_t a0, uint32_t a1, uint32_t b) {
  asm volatile("mma.sync.aligned.m16n8k8.row.col.f32.bf16.bf16.f32 {%0,%1,%2,%3}, {%4,%5}, {%6}, {%0,%1,%2,%3};"
               : "+f"(d0), "+f"(d1), "+f"(d2), "+f"(d3) : "r"(a0), "r"(a1), "r"(b));
}
__device__ __forceinline__ float rnd7(float x) { return __uint_as_float(__float_as_uint(x) + 0x8000u); }
__device__ __forceinline__ uint32_t set_tag(uint32_t v, uint32_t tag) { uint32_t r; asm("lop3.b32 %0, %1, 0xfffffffe, %2, 0xea;" : "=r"(r) : "r"(v), "r"(tag)); return r; }
__device__ __forceinline__ int tid_now() { int t; asm volatile("mov.u32 %0, %tid.x;" : "=r"(t)); return t; }
__device__ __forceinline__ void proxy_fence() { asm volatile("fence.proxy.async.shared::cta;" ::: "memory"); }

#define RDY_ID(h) ((0x540f >> (4 * (h))) & 15)
template <int V> struct IC { static constexpr int value = V; };

__global__ void __launch_bounds__(384, 1)
gqa_fused_kernel(const __grid_constant__ Params prm, __nv_bfloat16* __restrict__ out, uint32_t zero) {
  extern __shared__ __align__(1024) char smem[];
  const uint32_t sb = (uint32_t)__cvta_generic_to_shared(smem);
  const uint32_t qfull = sb + OFF_BAR, accrdy = qfull + 32, epochp = qfull + 40, xfull = qfull + 64, wofull = qfull + 128, kvfull = qfull + 384;
  const uint32_t dump = qfull + 1024, progp = qfull + 1280;
  const int warp = __shfl_sync(0xffffffff, threadIdx.x >> 5, 0);
  const int wg = warp >> 2, wiw = warp & 3;
  const int kvh = (blockIdx.x >> 3) & 7, bb = blockIdx.x & 7, blk = blockIdx.x >> 6, grp = blk * 8 + bb;
  const CUtensorMap* maps = prm.m + blk * 7;
  const int kvrow0 = (bb * 8 + kvh) * SK;

  auto issue_wq = [&](int d) {
    const uint32_t bar = qfull + 8 * (d & 3);
    mbar_expect_tx(bar, 2 * SLOT);
    tma3d(sb + OFF_RING + ((d + 2) & 3) * 2 * SLOT, maps + 3, d * 32, kvh * 8, bar);
  };
  auto issue_kv = [&](int i, int slot) {
    const uint32_t bar = kvfull + 8 * i;
    mbar_expect_tx(bar, i < 2 ? 8192 : KVS);
    asm volatile("cp.async.bulk.tensor.3d.shared::cluster.global.mbarrier::complete_tx::bytes.L2::cache_hint [%0], [%1, {%2, %3, %4}], [%5], %6;"
                 ::"r"(sb + OFF_RING + slot * KVS), "l"(maps + (i < 2 ? 5 : 1) + (i & 1)), "r"(0), "r"(kvrow0 + (i < 2 ? 0 : (i >> 1) * 48 - 32)), "r"(0), "r"(bar),
                   "l"(0x12F0000000000000ull) : "memory");
  };
  auto issue_wo = [&](int w) {
    const int p = (w >> 1) & 1, q = (w & 1) | ((w >> 1) & 2);
    int t = p + kvh + 1; if (kvh == 7) t = p; else if (t >= 7) t -= 7;
    const uint32_t bar = wofull + 8 * w;
    mbar_expect_tx(bar, SLOT);
    tma3d(sb + OFF_RING + ((w + 6) & 7) * SLOT, maps + 4, kvh * 512 + q * 128, t, bar);
  };

  if (elect()) {
    if (warp == 0) {
      if (sb & 1023) __trap();
      mbar_init(qfull, 1);
      issue_wq(0);
    } else if (warp == 3) {
      mbar_init(xfull, 1);
      mbar_expect_tx(xfull, XCH); tma3d(sb, maps, bb * SQ, 0, xfull);
    } else if (warp == 1) {
#pragma unroll
      for (int i = 1; i < 4; i++) mbar_init(qfull + 8 * i, 1);
    } else if (warp == 2) {
#pragma unroll
      for (int c = 1; c < 7; c++) mbar_init(xfull + 8 * c, 1);
    }
  }
  __syncthreads();
  if (warp == 2 && elect()) {
    issue_wq(1);
    mbar_expect_tx(xfull + 8, XCH); tma3d(sb + XCH, maps, bb * SQ, 1, xfull + 8);
    issue_wq(2); issue_wq(3);
    for (int c = 2; c < 7; c++) { mbar_expect_tx(xfull + 8 * c, XCH); tma3d(sb + c * XCH, maps, bb * SQ, c, xfull + 8 * c); }
  }
  if (warp >= 4 && elect()) {
    if (warp < 8) {
#pragma unroll
      for (int i = 0; i < 7; i++) mbar_init(wofull + 8 * ((warp - 4) * 7 + i), 1);
#pragma unroll
      for (int i = 0; i < 7; i++) if ((warp - 4) * 7 + i >= 8) mbar_expect_tx(wofull + 8 * ((warp - 4) * 7 + i), SLOT);
      if (warp == 4) mbar_init(accrdy, 4);
      if (warp == 5) {
        const uint32_t e = __ldcg(g_epoch + grp * 32);
        asm volatile("st.shared.u32 [%0], %1;" ::"r"(epochp), "r"(e) : "memory");
        if (blockIdx.x == 0) g_prog[(~e & 1) * 8].x = 0;
      }
    } else {
#pragma unroll
      for (int i = 0; i < 11; i++) mbar_init(kvfull + 8 * ((warp - 8) * 11 + i), 1);
    }
    proxy_fence();
  }
  __syncwarp();

  {
    const uint32_t ringlo = desc_lo(sb + OFF_RING, 2048), xlo = desc_lo(sb, 16);
    float a0[48], a1[48], a2[32], b0[16], b1[16];
    constexpr int ND = 14;
    auto duties = [&](int d) {
      if (!(wg == 2 && d == ND - 1)) nb_arrive(1 + (wg == 2 ? 0 : wg + 1), 256);
      if (warp == 9 && d >= 1) {
        if (elect()) {
          const int r = d - 1;
          if (r + 4 < ND) issue_wq(r + 4);
          else { issue_kv(r - 10, r - 10); if (r == 12) issue_kv(3, 3); }
        }
        __syncwarp();
      }
      if (warp == 1 && d + 1 < ND) {
        if (d & 1) mbar_wait(xfull + 8 * ((d + 1) >> 1), 0);
        mbar_wait(qfull + 8 * ((d + 1) & 3), ((d + 1) >> 2) & 1);
      }
      if (d == 0 && threadIdx.x < 160) {
        const int idx = threadIdx.x;
        l2_pull(dump + (idx & 31) * 4, prm.wq[blk] + kvh * 1024 + (size_t)(128 + (idx >> 2) * 8 + bb) * 8192 + (idx & 3) * 256);
      }
      const int tau = 3 * (d - 1) + wg, u = tau >> 1;
      if (wiw == 3 && d >= 1 && (tau & 1) && u < PF_U) {
        const int lane = threadIdx.x & 31;
        l2_pull(dump + lane * 4, prm.v[blk] + (size_t)(kvrow0 + (PF_J0 + (u | 1)) * 48 - 32) * 512 + (lane - ((u & 1) ? 0 : 32)) * 256);
      }
    };
    if (wg == 0) { mbar_wait(xfull, 0); mbar_wait(qfull, 0); }
    if (wg < 2) {
      for (int d = 0; d < ND; d++) {
        const uint32_t alo = ringlo + ((d + 2) & 3) * (2 * SLOT >> 4), xs = xlo + (((d >> 1) * XCH + (d & 1) * 64) >> 4);
        if (d + wg > 0) nb_sync(1 + wg, 256);
        WG_FENCE();
#pragma unroll
        for (int k = 0; k < 2; k++) {
          wgmma_ss_n96<1, 0>(a0, desc_mk(alo + wg * (8192 >> 4) + k * (2048 >> 4)), desc_mk(xs + k * 2), (d | k) != 0);
          wgmma_ss_n96<1, 0>(a1, desc_mk(alo + wg * (8192 >> 4) + ((4096 + k * 2048) >> 4)), desc_mk(xs + k * 2), (d | k) != 0);
          wgmma_ss_n64<1, 0>(a2, desc_mk(alo + (6 + wg) * (4096 >> 4) + k * (2048 >> 4)), desc_mk(xs + k * 2), (d | k) != 0);
        }
        WG_COMMIT();
        duties(d);
        WG_WAIT(0); fop(a0); fop(a1); fop(a2);
      }
    } else {
      for (int d = 0; d < ND; d++) {
        const uint32_t alo = ringlo + ((d + 2) & 3) * (2 * SLOT >> 4), xs = xlo + (((d >> 1) * XCH + (d & 1) * 64) >> 4);
        nb_sync(3, 256);
        WG_FENCE();
#pragma unroll
        for (int k = 0; k < 2; k++) {
          wgmma_ss_n96<1, 0>(a0, desc_mk(alo + ((4 * 4096 + k * 2048) >> 4)), desc_mk(xs + k * 2), (d | k) != 0);
          wgmma_ss_n96<1, 0>(a1, desc_mk(alo + ((5 * 4096 + k * 2048) >> 4)), desc_mk(xs + k * 2), (d | k) != 0);
          wgmma_ss_n32<1, 0>(b0, desc_mk(alo + ((6 * 4096 + k * 2048) >> 4)), desc_mk(xs + k * 2 + (64 * 128 >> 4)), (d | k) != 0);
          wgmma_ss_n32<1, 0>(b1, desc_mk(alo + ((7 * 4096 + k * 2048) >> 4)), desc_mk(xs + k * 2 + (64 * 128 >> 4)), (d | k) != 0);
        }
        WG_COMMIT();
        duties(d);
        WG_WAIT(0); fop(a0); fop(a1); fop(b0); fop(b1);
      }
    }
    __syncthreads();
    if (warp == 9 && elect()) issue_kv(4, 4);
    __syncwarp();
    {
      const int lane = tid_now() & 31;
      const int g = 2 * wiw + ((lane >> 3) & 1);
      const uint32_t base = sb + ((lane >> 4) * 8 + (lane & 7)) * 128 + ((g ^ (lane & 7)) << 4);
      const uint32_t t0 = base + (wg & 1) * 2 * QCH + (wg >> 1) * XCH;
#pragma unroll
      for (int j = 0; j < 12; j += 2) { stsm4t_acc(t0 + j * 1024, a0, 4 * j); stsm4t_acc(t0 + QCH + j * 1024, a1, 4 * j); }
      if (wg < 2) {
#pragma unroll
        for (int j = 0; j < 8; j += 2) stsm4t_acc(base + (2 + wg) * QCH + XCH + j * 1024, a2, 4 * j);
      } else {
#pragma unroll
        for (int j = 0; j < 4; j += 2) { stsm4t_acc(base + 2 * QCH + XCH + (8 + j) * 1024, b0, 4 * j); stsm4t_acc(base + 3 * QCH + XCH + (8 + j) * 1024, b1, 4 * j); }
      }
    }
    proxy_fence();
    if (warp == 1) mbar_wait(kvfull, 0);
    __syncthreads();
  }

  {
    const uint32_t qlo = desc_lo(sb + wg * 8192, 16);
    float o[N1 / 2], park[N2 / 2];
    float m0, m1, l0 = 0.f, l1 = 0.f;
    const float c = 0.0625f * 1.4426950408889634f;
    int ks = 0;
    auto release = [&](int i, int slot) {
      if (elect()) {
        if (i + 5 < 2 * NT) {
          uint32_t g;
          asm volatile("ld.volatile.shared.u32 %0, [%1];" : "=r"(g) : "r"(progp) : "memory");
          const int need = i * THR_K - THR_D - (kvh == 7 ? THR_7 : 0);
          if (i >= 8 && (int)g + THR_S < need) {
            uint32_t e; int n = 0;
            asm volatile("ld.shared.u32 %0, [%1];" : "=r"(e) : "r"(epochp));
            do { asm volatile("ld.relaxed.gpu.global.u32 %0, [%1];" : "=r"(g) : "l"(g_prog + (e & 1) * 8) : "memory"); } while ((int)g < need && ++n < 64);
          }
          issue_kv(i + 5, slot);
        } else if (i >= 40) { issue_wo(2 * i - 80); issue_wo(2 * i - 79); }
      }
      __syncwarp();
    };
    auto report = [&](int i) {
      if (i + 5 < 2 * NT && elect()) {
        uint32_t e;
        asm volatile("ld.shared.u32 %0, [%1];" : "=r"(e) : "r"(epochp));
        const uint4* pg = g_prog + (e & 1) * 8;
        asm volatile("red.relaxed.gpu.global.add.u32 [%0], 1;" ::"l"(pg) : "memory");
        asm volatile("cp.async.cg.shared.global [%0], [%1], 16;" ::"r"(progp), "l"(pg) : "memory");
      }
      __syncwarp();
    };
    auto step = [&](auto nc, int it) {
      constexpr int N = decltype(nc)::value;
      constexpr bool FIRST = (N == 16);
      float s[N / 2];
      const int vs = ks == 4 ? 0 : ks + 1;
      const uint32_t klo = desc_lo(sb + OFF_RING, 16) + ks * (KVS >> 4);
      if (!(FIRST && wg == 0)) nb_sync(1 + wg, 256);
      WG_FENCE();
#pragma unroll
      for (int kk = 0; kk < 16; kk++) {
        const uint64_t da = desc_mk(qlo + (((kk >> 2) * QCH + (kk & 3) * 32) >> 4)), db = desc_mk(klo + (((kk >> 2) * N * 128 + (kk & 3) * 32) >> 4));
        if constexpr (FIRST) wgmma_ss_n16<0, 0>(s, da, db, kk > 0); else wgmma_ss_n48<0, 0>(s, da, db, kk > 0);
      }
      WG_COMMIT();
      if (FIRST && wg == 0) nb_arrive(2, 256); else nb_arrive(wg == 0 ? 6 : (it == NT - 1 ? wg + 2 : wg + 3), 256);
      if (!FIRST && warp == 9) release(2 * it - 1, ks == 0 ? 4 : ks - 1);
      if (!FIRST && warp == 10) report(2 * it - 1);
      WG_WAIT(0); fop(s);
      float n0 = fmaxf(s[0], s[1]), n1 = fmaxf(s[2], s[3]);
#pragma unroll
      for (int i = 4; i < N / 2; i += 4) { n0 = fmaxf(n0, fmaxf(s[i], s[i + 1])); n1 = fmaxf(n1, fmaxf(s[i + 2], s[i + 3])); }
      n0 *= c; n1 *= c;
      if (FIRST || __any_sync(0xffffffffu, fmaxf(n0 - m0, n1 - m1) > 8.f)) {
        if (!FIRST) { n0 = fmaxf(n0, m0); n1 = fmaxf(n1, m1); }
        n0 = fmaxf(n0, __shfl_xor_sync(0xffffffffu, n0, 1)); n1 = fmaxf(n1, __shfl_xor_sync(0xffffffffu, n1, 1));
        n0 = fmaxf(n0, __shfl_xor_sync(0xffffffffu, n0, 2)); n1 = fmaxf(n1, __shfl_xor_sync(0xffffffffu, n1, 2));
        if (!FIRST) {
          const float a0 = ex2(m0 - n0), a1 = ex2(m1 - n1);
          l0 *= a0; l1 *= a1;
#pragma unroll
          for (int i = 0; i < N1 / 2; i += 4) { o[i] *= a0; o[i + 1] *= a0; o[i + 2] *= a1; o[i + 3] *= a1; }
#pragma unroll
          for (int i = 0; i < N2 / 2; i += 4) { park[i] *= a0; park[i + 1] *= a0; park[i + 2] *= a1; park[i + 3] *= a1; }
        }
        m0 = n0; m1 = n1;
      }
      uint32_t p[N / 4];
#pragma unroll
      for (int i = N / 2 - 4; i >= 0; i -= 4) {
        const float e0 = ex2(fmaf(s[i], c, -m0)), e1 = ex2(fmaf(s[i + 1], c, -m0)), e2 = ex2(fmaf(s[i + 2], c, -m1)), e3 = ex2(fmaf(s[i + 3], c, -m1));
        l0 += e0 + e1; l1 += e2 + e3;
        p[i / 2] = pack(e0, e1); p[i / 2 + 1] = pack(e2, e3);
      }
      if (!FIRST) fop(o);
      const uint32_t vlo = desc_lo(sb + OFF_RING, N * 128) + vs * (KVS >> 4);
      const uint32_t dep = (__float_as_uint(l0) | __float_as_uint(l1)) & zero;
      if (warp == 1) mbar_wait(kvfull + 8 * (2 * it + 1) + dep, 0);
      if (FIRST) nb_sync(4 + wg + dep, 256); else nb_sync((dep | 4) ^ wg, 256);
      float o2[N2 / 2];
      WG_FENCE();
#pragma unroll
      for (int kk = 0; kk < N / 16; kk++) {
        const uint64_t db = desc_mk(vlo + ((kk * 2048) >> 4)), db2 = desc_mk(vlo + ((kk * 2048 + 3 * N * 128 + (N1 - 192) * 2) >> 4));
        wgmma_rs_n232<1>(o, p[kk * 4], p[kk * 4 + 1], p[kk * 4 + 2], p[kk * 4 + 3], db, !FIRST);
        wgmma_rs_n24<1>(o2, p[kk * 4], p[kk * 4 + 1], p[kk * 4 + 2], p[kk * 4 + 3], db2, kk);
      }
      WG_COMMIT();
      if (it < NT - 1) nb_arrive(1 + (wg == 0 ? 2 : wg - 1), 256);
      else if (wg < 2) nb_arrive(5 + wg, 256);
      if (warp == 9) release(2 * it, ks);
      if (warp == 10) report(2 * it);
      if (warp == 1 && it + 1 < NT) mbar_wait(kvfull + 8 * (2 * it + 2), 0);
      ks = vs == 4 ? 0 : vs + 1;
      WG_WAIT(0); fop(o); fop(o2);
#pragma unroll
      for (int i = 0; i < N2 / 2; i++) { if (FIRST) asm volatile("mov.b32 %0, %1;" : "=f"(park[i]) : "f"(o2[i])); else park[i] += o2[i]; }
    };
    step(IC<16>(), 0);
#pragma unroll 1
    for (int it = 1; it < NT; it++) step(IC<48>(), it);
    if (wg < 2) nb_arrive(1, 384);
    else { nb_sync(1, 384); if (warp == 8 && elect()) { issue_wo(6); issue_wo(7); } __syncwarp(); }
    l0 += __shfl_xor_sync(0xffffffffu, l0, 1); l1 += __shfl_xor_sync(0xffffffffu, l1, 1);
    l0 += __shfl_xor_sync(0xffffffffu, l0, 2); l1 += __shfl_xor_sync(0xffffffffu, l1, 2);
    const float r0 = rcp(l0), r1 = rcp(l1);
    const int lane = tid_now() & 31;
    const uint32_t base = sb + (wg * 64 + wiw * 16 + (lane & 7) + ((lane >> 3) & 1) * 8) * 128;
#pragma unroll
    for (int j = 0; j < 32; j += 2) {
      float v[8];
#pragma unroll
      for (int i = 0; i < 8; i++) { const int q = 4 * j + i; v[i] = (q < N1 / 2 ? o[q < N1 / 2 ? q : 0] : park[q >= N1 / 2 ? q - N1 / 2 : 0]) * ((i & 2) ? r1 : r0); }
      const int g = j + (lane >> 4);
      stsm4(base + (j >> 3) * QCH + (((g & 7) ^ (lane & 7)) << 4), pack(v[0], v[1]), pack(v[2], v[3]), pack(v[4], v[5]), pack(v[6], v[7]));
    }
    proxy_fence();
    if (wg != 0) nb_arrive(1 + wg, 256);
  }

  {
    const int tw = tid_now() & 127, lane = tw & 31;
    uint32_t epoch;
    asm volatile("ld.shared.u32 %0, [%1];" : "=r"(epoch) : "r"(epochp));
    uint32_t tag = (epoch + 1) & 1;
    asm volatile("" : "+r"(tag));
    const uint32_t hand = sb + OFF_RING + 2 * SLOT;
    if (wg == 0) {
      uint32_t al = desc_lo(sb + OFF_RING, 2048), ol = desc_lo(sb, 16);
      float accA[48], accB[48];
      uint4* gsend = g_part + ((grp * 7 + (kvh == 7 ? 0 : kvh + 1)) * 8 + kvh) * 768 + tw;
      const int wrap = kvh == 7 ? 7 : 6 - kvh;
      uint64_t pk[12];
      auto packup = [&](float (&acc)[48]) {
#pragma unroll
        for (int i = 0; i < 12; i++)
          pk[i] = (uint64_t)set_tag(pack(rnd7(acc[4 * i]), acc[4 * i + 1]), tag) | ((uint64_t)pack(acc[4 * i + 2], acc[4 * i + 3]) << 32);
      };
      auto send = [&](int p, int i0, int i1) {
        uint4* pp = gsend + (p >= wrap ? p - 7 : p) * (8 * 768);
#pragma unroll
        for (int i = i0; i < i1; i++)
          asm volatile("st.relaxed.gpu.global.v2.b64 [%0], {%1,%2};" ::"l"(pp + i * 128), "l"(pk[2 * i]), "l"(pk[2 * i + 1]) : "memory");
      };
      auto chunk = [&](float (&acc)[48], int L0, int c, int q) {
        if ((c & 1) == 0 && c > 0) nb_sync(RDY_ID((c >> 1) & 3), 160);
        WG_FENCE();
#pragma unroll
        for (int ks = 0; ks < 8; ks++)
          wgmma_ss_n96<1, 0>(acc, desc_mk(al + ((c + 6) & 7) * (SLOT >> 4) + ks * (2048 >> 4)),
                             desc_mk(ol + (((2 * (q & 1) + (ks >> 2)) * QCH + (q >> 1) * XCH + (ks & 3) * 32) >> 4)), (q | ks) != 0);
        WG_COMMIT();
        WG_WAIT(1);
        if (c > 0 && L0 + c <= 20) nb_arrive(7 + ((c - 1) & 7), 160);
        asm volatile("add.u32 %0, %0, %1;" : "+r"(al) : "r"(zero)); asm volatile("add.u32 %0, %0, %1;" : "+r"(ol) : "r"(zero));
      };
      mbar_wait(wofull, 0); mbar_wait(wofull + 8, 0);
      nb_sync(2, 256);
      chunk(accA, 0, 0, 0); chunk(accA, 0, 1, 1); chunk(accB, 0, 2, 0); chunk(accB, 0, 3, 1);
      nb_sync(3, 256);
      chunk(accA, 0, 4, 2); chunk(accA, 0, 5, 3);
      chunk(accB, 0, 6, 2); fop(accA); packup(accA); send(0, 0, 3);
      chunk(accB, 0, 7, 3); send(0, 3, 6);
      chunk(accA, 0, 8, 0); fop(accB); packup(accB); send(1, 0, 3);
#pragma unroll 1
      for (int p = 2; p < 6; p += 2) {
        chunk(accA, 4 * p, 1, 1); send(p - 1, 3, 6);
        chunk(accA, 4 * p, 2, 2); chunk(accA, 4 * p, 3, 3);
        chunk(accB, 4 * p, 4, 0); fop(accA); packup(accA); send(p, 0, 3);
        chunk(accB, 4 * p, 5, 1); send(p, 3, 6);
        chunk(accB, 4 * p, 6, 2); chunk(accB, 4 * p, 7, 3);
        chunk(accA, 4 * p, 8, 0); fop(accB); packup(accB); send(p + 1, 0, 3);
      }
      send(5, 3, 6);
      chunk(accA, 24, 1, 1); chunk(accA, 24, 2, 2); chunk(accA, 24, 3, 3);
      WG_WAIT(0); fop(accA);
      if (kvh == 7) { packup(accA); send(6, 0, 6); }
      else {
#pragma unroll
        for (int i = 0; i < 12; i++)
          asm volatile("st.shared.v4.f32 [%0], {%1,%2,%3,%4};" ::"r"(hand + (i * 128 + tw) * 16),
                       "f"(accA[4 * i]), "f"(accA[4 * i + 1]), "f"(accA[4 * i + 2]), "f"(accA[4 * i + 3]) : "memory");
        __syncwarp();
        if (elect()) mbar_arrive(accrdy);
      }
    } else if (warp == 7) {
#pragma unroll 1
      for (int h = 1; h < 14; h++) {
        mbar_wait(wofull + 16 * h, 0);
        mbar_wait(wofull + 16 * h + 8, 0);
        nb_arrive(RDY_ID(h & 3), 160);
      }
    } else if (warp == 6) {
      const int p = (lane >> 2) + 2, q = lane & 3;
      int t = p + kvh + 1; if (kvh == 7) t = p; else if (t >= 7) t -= 7;
      const int cc = (kvh * 512 + q * 128) | t;
#pragma unroll 1
      for (int L = 0; L + 8 < NWO; L++) {
        const int c = __shfl_sync(0xffffffffu, cc, L);
        const uint32_t dst = sb + OFF_RING + ((L + 6) & 7) * SLOT, bar = wofull + 8 * (L + 8);
        nb_sync(7 + (L & 7), 160);
        if (elect()) tma3d(dst, maps + 4, c & ~7, c & 7, bar);
        __syncwarp();
      }
    } else if (kvh != 7) {
      const int f = warp >= 8 ? warp - 8 : warp;
      auto src_of = [&](int k) {
        const int k7 = kvh > 0 ? kvh - 1 : 0;
        int sidx = kvh - 1 - (k > k7 ? k - 1 : k); if (sidx < 0) sidx += 7;
        return k == k7 ? 7 : sidx;
      };
      const uint4* gown = g_part + (grp * 7 + kvh) * 8 * 768 + f * 128;
      const uint4* pprobe = gown + src_of(lane < 7 ? lane : 0) * 768 + 127;
      const uint32_t hu = hand + f * 4096;
      const uint32_t ident = (lane >> 3) == (lane & 3) ? (0x3f80u << (((lane >> 2) & 1) * 16)) : 0u;
      uint4 v[7][4];
      int spins = 0;
      auto fetch = [&](uint4 (&d)[4], int k) {
        const uint4* pp = gown + src_of(k) * 768 + lane;
#pragma unroll
        for (int i = 0; i < 4; i++) {
          uint64_t a, b;
          asm volatile("ld.relaxed.gpu.global.v2.b64 {%0,%1}, [%2];" : "=l"(a), "=l"(b) : "l"(pp + i * 32) : "memory");
          d[i] = make_uint4((uint32_t)a, (uint32_t)(a >> 32), (uint32_t)b, (uint32_t)(b >> 32));
        }
      };
      auto untag = [&](uint4 (&d)[4]) {
        uint32_t bad = 0;
#pragma unroll
        for (int i = 0; i < 4; i++) { d[i].x ^= tag; d[i].z ^= tag; bad |= d[i].x | d[i].z; }
        return bad;
      };
      auto refetch = [&](uint4 (&d)[4], int k, uint32_t bad) {
        while (__any_sync(0xffffffffu, bad & 1)) {
          fetch(d, k);
          bad = untag(d);
          if (++spins > 8000000) __trap();
        }
      };
      uint32_t seen = 0;
      auto probe = [&]() {
        uint32_t pr;
        asm volatile("ld.relaxed.gpu.global.u32 %0, [%1];" : "=r"(pr) : "l"(pprobe) : "memory");
        seen = __ballot_sync(0xffffffffu, ((pr ^ tag) & 1) == 0);
        if (++spins > 8000000) __trap();
      };
#pragma unroll
      for (int k = 0; k < 6; k++) {
        while (!((seen >> k) & 1)) probe();
        fetch(v[k], k);
      }
      while (!(seen & 64)) {
        uint32_t ok;
        asm volatile("{\n.reg .pred P;\nmbarrier.test_wait.parity.shared::cta.b64 P, [%1], 0;\nselp.u32 %0,1,0,P;\n}" : "=r"(ok) : "r"(accrdy) : "memory");
        if (__any_sync(0xffffffffu, ok)) break;
        probe();
      }
      const bool early = seen & 64;
      if (early) fetch(v[6], 6);
      float sum[32];
#pragma unroll
      for (int i = 0; i < 32; i++) sum[i] = 0.f;
      {
        uint32_t bad = 0;
#pragma unroll
        for (int k = 0; k < 6; k++) bad |= untag(v[k]);
        if (__any_sync(0xffffffffu, bad & 1)) {
#pragma unroll
          for (int k = 0; k < 6; k++) refetch(v[k], k, v[k][0].x | v[k][0].z | v[k][1].x | v[k][1].z | v[k][2].x | v[k][2].z | v[k][3].x | v[k][3].z);
        }
      }
#pragma unroll
      for (int k = 0; k < 7; k++) {
        if (k == 6) {
          mbar_wait(accrdy, 0);
#pragma unroll
          for (int i = 0; i < 8; i++) {
            float4 x;
            asm volatile("ld.shared.v4.f32 {%0,%1,%2,%3}, [%4];" : "=f"(x.x), "=f"(x.y), "=f"(x.z), "=f"(x.w) : "r"(hu + (i & 1) * 2048 + (i >> 1) * 512 + lane * 16) : "memory");
            sum[4 * i] += x.x; sum[4 * i + 1] += x.y; sum[4 * i + 2] += x.z; sum[4 * i + 3] += x.w;
          }
          if (!early) fetch(v[6], 6);
          refetch(v[6], 6, untag(v[6]));
        }
#pragma unroll
        for (int i = 0; i < 4; i++) {
          mma_add(sum[8 * i], sum[8 * i + 1], sum[8 * i + 2], sum[8 * i + 3], v[k][i].x, v[k][i].y, ident);
          mma_add(sum[8 * i + 4], sum[8 * i + 5], sum[8 * i + 6], sum[8 * i + 7], v[k][i].z, v[k][i].w, ident);
        }
      }
      __syncwarp();
      const int r = (lane >> 4) * 8 + (lane & 7), h = (lane >> 3) & 1;
#pragma unroll
      for (int k = 0; k < 4; k++) stsm4t_acc(hu + r * 128 + (((2 * k + h) ^ (r & 7)) << 4), sum, 8 * k);
      __syncwarp();
      __nv_bfloat16* ob = out + (size_t)(bb * SQ + f * 16 + (lane >> 3)) * (2 * DM) + blk * DM + kvh * 64 + (lane & 7) * 8;
#pragma unroll
      for (int k = 0; k < 4; k++) {
        const int row = k * 4 + (lane >> 3);
        uint4 x;
        asm volatile("ld.shared.v4.u32 {%0,%1,%2,%3}, [%4];" : "=r"(x.x), "=r"(x.y), "=r"(x.z), "=r"(x.w) : "r"(hu + row * 128 + (((lane & 7) ^ (row & 7)) << 4)) : "memory");
        *reinterpret_cast<uint4*>(ob + (size_t)(k * 4) * (2 * DM)) = x;
      }
      if (kvh == 0 && warp == 9 && lane == 0) g_epoch[grp * 32] = epoch + 1;
    }
  }
}

typedef CUresult (*EncodeFn)(CUtensorMap*, CUtensorMapDataType, cuuint32_t, void*, const cuuint64_t*, const cuuint64_t*, const cuuint32_t*,
                             const cuuint32_t*, CUtensorMapInterleave, CUtensorMapSwizzle, CUtensorMapL2promotion, CUtensorMapFloatOOBfill);

void make_map(EncodeFn fn, CUtensorMap* m, void* ptr, uint64_t rows, uint64_t cols, uint32_t brows, uint32_t bchunks) {
  cuuint64_t dims[3] = {64, rows, cols / 64};
  cuuint64_t strides[2] = {cols * 2, 128};
  cuuint32_t box[3] = {64, brows, bchunks};
  cuuint32_t es[3] = {1, 1, 1};
  fn(m, CU_TENSOR_MAP_DATA_TYPE_BFLOAT16, 3, ptr, dims, strides, box, es, CU_TENSOR_MAP_INTERLEAVE_NONE, CU_TENSOR_MAP_SWIZZLE_128B,
     rows == 65536 ? CU_TENSOR_MAP_L2_PROMOTION_L2_256B : CU_TENSOR_MAP_L2_PROMOTION_L2_128B, CU_TENSOR_MAP_FLOAT_OOB_FILL_NONE);
}

}

extern "C" void kernel_launch(void* const* d_in, const int* in_sizes, int n_in, void* d_out, int out_size) {
  static EncodeFn fn = nullptr;
  if (!fn) {
    void* p = nullptr; cudaDriverEntryPointQueryResult qr;
    cudaGetDriverEntryPoint("cuTensorMapEncodeTiled", &p, cudaEnableDefault, &qr);
    fn = (EncodeFn)p;
    cudaFuncSetAttribute(gqa_fused_kernel, cudaFuncAttributeMaxDynamicSharedMemorySize, SMEM_BYTES);
  }
  Params prm;
  for (int b = 0; b < 2; b++) {
    make_map(fn, &prm.m[b * 7 + 0], d_in[b * 5 + 0], 768, 448, 96, 1);
    make_map(fn, &prm.m[b * 7 + 1], d_in[b * 5 + 1], 65536, 256, 48, 4);
    make_map(fn, &prm.m[b * 7 + 2], d_in[b * 5 + 2], 65536, 256, 48, 4);
    make_map(fn, &prm.m[b * 7 + 3], d_in[b * 5 + 3], 448, 4096, 32, 8);
    make_map(fn, &prm.m[b * 7 + 4], d_in[b * 5 + 4], 4096, 448, 128, 1);
    make_map(fn, &prm.m[b * 7 + 5], d_in[b * 5 + 1], 65536, 256, 16, 4);
    make_map(fn, &prm.m[b * 7 + 6], d_in[b * 5 + 2], 65536, 256, 16, 4);
    prm.v[b] = (const char*)d_in[b * 5 + 2];
    prm.wq[b] = (const char*)d_in[b * 5 + 3];
  }
  gqa_fused_kernel<<<128, 384, SMEM_BYTES, cudaStreamPerThread>>>(prm, (__nv_bfloat16*)d_out, 0u);
}
```
